```python
import torch

def _softmax(x, axis=-1):
    return torch.softmax(x, dim=axis)
def _gelu(x):
    return torch.nn.functional.gelu(x, approximate="tanh")
def _silu(x):
    return torch.nn.functional.silu(x)
def _sigmoid(x):
    return torch.sigmoid(x)
def _layernorm(x, axis=-1, eps=1e-5):
    m = x.mean(dim=axis, keepdim=True)
    v = x.var(dim=axis, keepdim=True, unbiased=False)
    return (x - m) / torch.sqrt(v + eps)
def _scatter_add(tgt, idx, src, axis=0):
    return tgt.clone().index_add_(axis, idx, src)
def _segment_sum(src, seg, n):
    out = torch.zeros((n,) + src.shape[1:], dtype=src.dtype)
    return out.index_add_(0, seg, src)
def _pad(x, pw):
    flat = tuple(v for pair in reversed(pw) for v in pair)
    return torch.nn.functional.pad(x, flat)

kernel_name = 'sequential_preLN__ssm_conv_s4__glu_gated_swiglu__prompt'

def setup_inputs():

    _w = (lambda a: (lambda t: t.to(torch.bfloat16) if t.is_floating_point() else t)(torch.as_tensor(a)))
    def _A_setup():
        B, L, D, N = 1, 2048, 576, 128
        A_re = -(lambda _x: torch.exp(torch.as_tensor(_x)))((lambda *s: torch.randn(*s, dtype=torch.bfloat16) * 6.4)(D, N))
        A_im = torch.pi * (lambda *s: torch.randn(*s, dtype=torch.bfloat16) * 0.05)(D, N)
        B_re = (lambda *s: torch.randn(*s, dtype=torch.bfloat16) * 0.05)(D, N)
        B_im = (lambda *s: torch.randn(*s, dtype=torch.bfloat16) * 0.05)(D, N)
        C_re = (lambda *s: torch.randn(*s, dtype=torch.bfloat16) * 0.05)(D, N)
        C_im = (lambda *s: torch.randn(*s, dtype=torch.bfloat16) * 0.05)(D, N)
        log_dt = (lambda *s: torch.randn(*s, dtype=torch.bfloat16) * 0.05)(D) * 0.5 - 4.0
        Dskip = (lambda *s: torch.randn(*s, dtype=torch.bfloat16) * 0.05)(D)
        return {
            "u": _w((lambda *s: torch.randn(*s, dtype=torch.bfloat16) * 0.05)(B, L, D)),
            "A_re": _w(A_re),
            "A_im": _w(A_im),
            "B_re": _w(B_re),
            "B_im": _w(B_im),
            "C_re": _w(C_re),
            "C_im": _w(C_im),
            "log_dt": _w(log_dt),
            "Dskip": _w(Dskip),
        }
    _A_in = _A_setup()

    def _B_setup():
        B, S, D, F = 1, 2048, 576, 4608
        return {
            "x": _w((lambda *s: torch.randn(*s, dtype=torch.bfloat16) * 0.05)(B, S, D)),
            "w1": _w((lambda *s: torch.randn(*s, dtype=torch.bfloat16) * 0.4)(D, F) * (2.0 / D) ** 0.5),
            "w3": _w((lambda *s: torch.randn(*s, dtype=torch.bfloat16) * 0.4)(D, F) * (2.0 / D) ** 0.5),
            "w2": _w((lambda *s: torch.randn(*s, dtype=torch.bfloat16) * 0.4)(F, D) * (2.0 / F) ** 0.5),
        }
    _B_in = _B_setup()

    return {
        "A_u": _A_in["u"],
        "A_A_re": _A_in["A_re"],
        "A_A_im": _A_in["A_im"],
        "A_B_re": _A_in["B_re"],
        "A_B_im": _A_in["B_im"],
        "A_C_re": _A_in["C_re"],
        "A_C_im": _A_in["C_im"],
        "A_log_dt": _A_in["log_dt"],
        "A_Dskip": _A_in["Dskip"],
        "B_x": _B_in["x"],
        "B_w1": _B_in["w1"],
        "B_w3": _B_in["w3"],
        "B_w2": _B_in["w2"],
    }

def reference(A_u, A_A_re, A_A_im, A_B_re, A_B_im, A_C_re, A_C_im, A_log_dt, A_Dskip, B_x, B_w1, B_w3, B_w2):
    def _A_ref(u, A_re, A_im, B_re, B_im, C_re, C_im, log_dt, Dskip):
        Bsz, L, D = u.shape
        dt = torch.exp(log_dt)[:, None]
        A = A_re + 1j * A_im
        Bc = B_re + 1j * B_im
        Cc = C_re + 1j * C_im
        logdA = dt * A
        dB = dt * Bc
        l = (lambda x, dt: x.to(dt))(torch.arange(L), A_re.dtype)
        P = torch.exp(logdA[:, :, None] * l[None, None, :])
        K = torch.einsum("dn,dnl,dn->dl", Cc, P, dB).real
        L2 = 2 * L
        Kp = _pad(K, ((0, 0), (0, L)))
        up = (lambda x, *d: x.permute(*d))(u, 0, 2, 1)
        up = _pad(up, ((0, 0), (0, 0), (0, L)))
        Kf = (lambda x, axes=(-2,-1): torch.fft.rfft2(x.float(), dim=axes))(Kp[:, None, :], axes=(-2, -1))
        Uf = (lambda x, axes=(-2,-1): torch.fft.rfft2(x.float(), dim=axes))(up[:, :, None, :], axes=(-2, -1))
        Yf = Uf * Kf[None, :, :, :]
        y = (lambda x, s, axes=(-2,-1): torch.fft.irfft2(x, s=s, dim=axes).to(torch.bfloat16))(Yf, (1, L2), axes=(-2, -1))[:, :, 0, :L]
        y = (lambda x, *d: x.permute(*d))(y, 0, 2, 1) + u * Dskip[None, None, :]
        return y

    def _B_ref(x, w1, w3, w2):
        gate = torch.einsum("bsd,df->bsf", x, w1)
        up = torch.einsum("bsd,df->bsf", x, w3)
        h = _silu(gate) * up
        out = torch.einsum("bsf,fd->bsd", h, w2)
        return out

    x = A_u
    h = x + _A_ref(_layernorm(x, axis=-1), A_A_re, A_A_im, A_B_re, A_B_im, A_C_re, A_C_im, A_log_dt, A_Dskip)
    h2 = h + _B_ref(_layernorm(h, axis=-1), B_w1, B_w3, B_w2)
    return h2
```

```cpp
#include <cuda_runtime.h>
#include <cuda_bf16.h>
#include <cuda.h>
#include <stdint.h>
#include <string.h>

namespace {

constexpr int kL = 2048, kD = 576, kF = 4608, kN = 128;

}

__device__ __align__(1024) __nv_bfloat16 g_hT[kD * kL];
__device__ uint4 g_part[16 * 9 * 9 * 1024];
__device__ unsigned g_flag[16 * 9 * 8];
__device__ uint4 g_ux[kD * 512];
__device__ unsigned g_lncnt;

namespace {

__device__ __forceinline__ uint32_t smem_u32(const void* p) { return (uint32_t)__cvta_generic_to_shared(p); }
__device__ __forceinline__ void mbar_init(uint32_t b, int c) {
  asm volatile("mbarrier.init.shared::cta.b64 [%0], %1;" ::"r"(b), "r"(c));
}
__device__ __forceinline__ void mbar_expect(uint32_t b, int bytes) {
  asm volatile("mbarrier.arrive.expect_tx.shared::cta.b64 _, [%0], %1;" ::"r"(b), "r"(bytes) : "memory");
}
__device__ __forceinline__ void mbar_arrive(uint32_t b) {
  asm volatile("mbarrier.arrive.shared::cta.b64 _, [%0];" ::"r"(b) : "memory");
}
__device__ __forceinline__ void mbar_arrive_cluster(uint32_t b) {
  asm volatile("mbarrier.arrive.shared::cluster.b64 _, [%0];" ::"r"(b) : "memory");
}
__device__ __forceinline__ uint32_t mapa(uint32_t a, uint32_t rank) {
  uint32_t r;
  asm volatile("mapa.shared::cluster.u32 %0, %1, %2;" : "=r"(r) : "r"(a), "r"(rank));
  return r;
}
__device__ __forceinline__ void mbar_wait(uint32_t b, uint32_t parity) {
  asm volatile(
      "{\n.reg .pred p;\n.reg .u32 n;\n"
      "mbarrier.try_wait.parity.shared::cta.b64 p, [%0], %1;\n"
      "@p bra DONE;\n"
      "mov.u32 n, 0;\n"
      "LOOP:\n"
      "mbarrier.try_wait.parity.shared::cta.b64 p, [%0], %1;\n"
      "@p bra DONE;\n"
      "add.u32 n, n, 1;\n"
      "setp.lt.u32 p, n, 4000000;\n"
      "@p bra LOOP;\n"
      "trap;\n"
      "DONE:\n}\n" ::"r"(b), "r"(parity) : "memory");
}
__device__ __forceinline__ void flag_wait(const unsigned* p, unsigned target) {
  unsigned v;
  for (int it = 0; it < 4000000; it++) {
    asm volatile("ld.acquire.gpu.global.u32 %0, [%1];" : "=r"(v) : "l"(p) : "memory");
    if (v >= target) return;
    __nanosleep(64);
  }
  __trap();
}
__device__ __forceinline__ void tma2d(uint32_t dst, const CUtensorMap* tm, uint32_t bar, int x, int y) {
  asm volatile("cp.async.bulk.tensor.2d.shared::cluster.global.mbarrier::complete_tx::bytes [%0], [%1, {%3, %4}], [%2];"
               ::"r"(dst), "l"(tm), "r"(bar), "r"(x), "r"(y) : "memory");
}
__device__ __forceinline__ void tma2d_mc(uint32_t dst, const CUtensorMap* tm, uint32_t bar, int x, int y) {
  asm volatile("cp.async.bulk.tensor.2d.shared::cluster.global.mbarrier::complete_tx::bytes.multicast::cluster [%0], [%1, {%3, %4}], [%2], %5;"
               ::"r"(dst), "l"(tm), "r"(bar), "r"(x), "r"(y), "h"((uint16_t)3) : "memory");
}
__device__ __forceinline__ void bulk_g2s(uint32_t dst, const void* src, int bytes, uint32_t bar) {
  asm volatile("cp.async.bulk.shared::cluster.global.mbarrier::complete_tx::bytes [%0], [%1], %2, [%3];"
               ::"r"(dst), "l"(src), "r"(bytes), "r"(bar) : "memory");
}
__device__ __forceinline__ void ldsm4t(uint32_t* r, uint32_t a) {
  asm volatile("ldmatrix.sync.aligned.m8n8.x4.trans.shared.b16 {%0,%1,%2,%3}, [%4];"
               : "=r"(r[0]), "=r"(r[1]), "=r"(r[2]), "=r"(r[3]) : "r"(a) : "memory");
}
__device__ __forceinline__ void stsm4(uint32_t a, uint32_t r0, uint32_t r1, uint32_t r2, uint32_t r3) {
  asm volatile("stmatrix.sync.aligned.m8n8.x4.shared.b16 [%0], {%1,%2,%3,%4};" ::"r"(a), "r"(r0), "r"(r1), "r"(r2), "r"(r3) : "memory");
}
__device__ __forceinline__ void lds128(uint32_t* r, uint32_t a) {
  asm volatile("ld.shared.v4.u32 {%0,%1,%2,%3}, [%4];" : "=r"(r[0]), "=r"(r[1]), "=r"(r[2]), "=r"(r[3]) : "r"(a) : "memory");
}
__device__ __forceinline__ void sts128(uint32_t a, const uint32_t* r) {
  asm volatile("st.shared.v4.u32 [%0], {%1,%2,%3,%4};" ::"r"(a), "r"(r[0]), "r"(r[1]), "r"(r[2]), "r"(r[3]) : "memory");
}
__device__ __forceinline__ void stg128(void* p, const uint32_t* r) {
  asm volatile("st.global.v4.u32 [%0], {%1,%2,%3,%4};" ::"l"(p), "r"(r[0]), "r"(r[1]), "r"(r[2]), "r"(r[3]) : "memory");
}
__device__ __forceinline__ uint32_t pack_bf16(float lo, float hi) {
  uint32_t r;
  asm("cvt.rn.bf16x2.f32 %0, %1, %2;" : "=r"(r) : "f"(hi), "f"(lo));
  return r;
}
__device__ __forceinline__ float bf_lo(uint32_t v) { return __uint_as_float(v << 16); }
__device__ __forceinline__ float bf_hi(uint32_t v) { return __uint_as_float(v & 0xffff0000u); }
__device__ __forceinline__ float round_bf16(float v) { return __bfloat162float(__float2bfloat16(v)); }
__device__ __forceinline__ uint32_t mul_bf16x2(uint32_t a, uint32_t b) {
  uint32_t r;
  asm("mul.rn.bf16x2 %0, %1, %2;" : "=r"(r) : "r"(a), "r"(b));
  return r;
}
__device__ __forceinline__ uint32_t sub_bf16x2(uint32_t a, uint32_t b) {
  uint32_t r;
  asm("sub.rn.bf16x2 %0, %1, %2;" : "=r"(r) : "r"(a), "r"(b));
  return r;
}
__device__ __forceinline__ float ex2f(float x) { float r; asm("ex2.approx.ftz.f32 %0, %1;" : "=f"(r) : "f"(x)); return r; }
__device__ __forceinline__ float rcpf(float x) { float r; asm("rcp.approx.ftz.f32 %0, %1;" : "=f"(r) : "f"(x)); return r; }

#define ACC32(c, d)                                                                                        \
  c(d[0]), c(d[1]), c(d[2]), c(d[3]), c(d[4]), c(d[5]), c(d[6]), c(d[7]), c(d[8]), c(d[9]), c(d[10]),      \
      c(d[11]), c(d[12]), c(d[13]), c(d[14]), c(d[15]), c(d[16]), c(d[17]), c(d[18]), c(d[19]), c(d[20]),  \
      c(d[21]), c(d[22]), c(d[23]), c(d[24]), c(d[25]), c(d[26]), c(d[27]), c(d[28]), c(d[29]), c(d[30]), c(d[31])
#define REGS32                                                                                             \
  "{%0,%1,%2,%3,%4,%5,%6,%7,%8,%9,%10,%11,%12,%13,%14,%15,%16,%17,%18,%19,%20,%21,%22,%23,%24,%25,%26,%27,%28,%29,%30,%31}"

template <bool FIRST, int OFF>
__device__ __forceinline__ void wgmma64(float (&d)[32], const uint32_t* a, uint32_t dlo) {
  if constexpr (FIRST) {
    asm volatile("{\n.reg .pred p;\n.reg .b32 t;\n.reg .b64 db;\nsetp.ne.b32 p, 0, 0;\nadd.u32 t, %36, %37;\nmov.b64 db, {t, 0x40000040};\n"
                 "wgmma.mma_async.sync.aligned.m64n64k16.f32.bf16.bf16 " REGS32 ", {%32,%33,%34,%35}, db, p, 1, 1, 1;\n}\n"
                 : ACC32("=f", d) : "r"(a[0]), "r"(a[1]), "r"(a[2]), "r"(a[3]), "r"(dlo), "n"(OFF));
  } else {
    asm volatile("{\n.reg .pred p;\n.reg .b32 t;\n.reg .b64 db;\nsetp.eq.b32 p, 0, 0;\nadd.u32 t, %36, %37;\nmov.b64 db, {t, 0x40000040};\n"
                 "wgmma.mma_async.sync.aligned.m64n64k16.f32.bf16.bf16 " REGS32 ", {%32,%33,%34,%35}, db, p, 1, 1, 1;\n}\n"
                 : ACC32("+f", d) : "r"(a[0]), "r"(a[1]), "r"(a[2]), "r"(a[3]), "r"(dlo), "n"(OFF));
  }
}
__device__ __forceinline__ void wg_fence() { asm volatile("wgmma.fence.sync.aligned;" ::: "memory"); }
__device__ __forceinline__ void wg_commit() { asm volatile("wgmma.commit_group.sync.aligned;" ::: "memory"); }
template <int N>
__device__ __forceinline__ void wg_wait() { asm volatile("wgmma.wait_group.sync.aligned %0;" ::"n"(N) : "memory"); }
__device__ __forceinline__ void pin(float& v) { asm volatile("" : "+f"(v)::"memory"); }
__device__ __forceinline__ void pin(uint32_t& v) { asm volatile("" : "+r"(v)::"memory"); }

constexpr int kSlotBytes = 12288, kPasses = 27;
constexpr uint32_t oR = 0, kRWg = 9 * 8192, oW = 2 * kRWg, oBar = oW + 6 * kSlotBytes;
constexpr uint32_t bFull = oBar, bEmpty = bFull + 48, bX = bEmpty + 48, bGo = bX + 48, bP0 = bGo + 8, oK = bP0 + 8, oEnd = oK + 256;
constexpr int kFfnSmem = oEnd;
constexpr uint32_t kSentinel = 0xffffffffu;

__device__ __forceinline__ uint4* part_ptr(int mt, int blk, int slot) { return g_part + ((mt * 9 + blk) * 9 + slot) * 1024; }

#define PROBE "test_wait"
#define NRESET 8
struct Ctx {
  uint32_t sb;
  uint32_t relbar;
  bool rel, always;
  uint32_t priv;
  float c0, c1;
  uint32_t ready;
  const uint4* src;
  uint4* dst;
};

__device__ __forceinline__ uint32_t mbar_probe(uint32_t b, uint32_t parity) {
  uint32_t ok;
  asm volatile("{\n.reg .pred p;\nmbarrier." PROBE ".parity.shared::cta.b64 p, [%1], %2;\nselp.u32 %0, 1, 0, p;\n}\n"
               : "=r"(ok) : "r"(b), "r"(parity) : "memory");
  return ok;
}
__device__ __forceinline__ uint32_t frag_index() { return (threadIdx.x >> 5) * 128 + (threadIdx.x & 31); }
__device__ __forceinline__ void ldg_relaxed(uint32_t* v, const uint4* p) {
  asm volatile("ld.relaxed.gpu.global.v4.u32 {%0,%1,%2,%3}, [%4];" : "=r"(v[0]), "=r"(v[1]), "=r"(v[2]), "=r"(v[3]) : "l"(p) : "memory");
}
__device__ __forceinline__ void stg_relaxed(uint4* p, const uint32_t* v) {
  asm volatile("st.relaxed.gpu.global.v4.u32 [%0], {%1,%2,%3,%4};" ::"l"(p), "r"(v[0]), "r"(v[1]), "r"(v[2]), "r"(v[3]) : "memory");
}
__device__ __forceinline__ bool has_sentinel(const uint32_t* v) { return max(max(v[0], v[1]), max(v[2], v[3])) == kSentinel; }
__device__ __forceinline__ void ensure_landed(uint32_t* v, const uint4* p) {
#pragma unroll 1
  for (int it = 0; it < 2000000 && has_sentinel(v); it++) ldg_relaxed(v, p);
}
__device__ __forceinline__ void load_tile(uint32_t (&v)[16], const uint4* p) {
#pragma unroll
  for (int q = 0; q < 4; q++) ldg_relaxed(&v[4 * q], p + q * 32);
}
__device__ __forceinline__ void ensure_tile(uint32_t (&v)[16], const uint4* p) {
#pragma unroll 1
  for (int it = 0; it < 2000000; it++) {
    uint32_t m = v[0];
#pragma unroll
    for (int i = 1; i < 16; i++) m = max(m, v[i]);
    if (!__any_sync(0xffffffffu, m == kSentinel)) break;
    load_tile(v, p);
  }
}
template <typename T>
__device__ __forceinline__ void pinp(T*& v) { asm volatile("" : "+l"(v)::"memory"); }

enum Kind { K_FIRST, K_GATE, K_UP, K_XCHG };

template <int KIND, int S>
__device__ __forceinline__ void epi_slice(Ctx& c, uint32_t (&A)[144], float (&p)[32], uint32_t (&Sv)[16], int n, int mt, int f) {
  if constexpr (KIND == K_FIRST) {
    if (S < 5) {
#pragma unroll
      for (int i = 24 * S + 24; i < 24 * S + 48; i++) { A[i] = sub_bf16x2(A[i], Sv[i & 1]); pin(A[i]); }
    }
    if (S == 2) {
#pragma unroll
      for (int q = 0; q < 4; q++) sts128(c.priv + 8 * 8192 + q * 512, (uint32_t*)&p[4 * q]);
    }
  } else if constexpr (KIND == K_GATE) {
    if (S >= 1 && n == 8) {
#pragma unroll
      for (int q = 6 * (S - 1); q < 6 * S; q++) lds128(&A[4 * q], c.priv + (q >> 2) * 8192 + (q & 3) * 512);
    }
    constexpr int lo = S < 4 ? S * 3 : 4 + S * 2, hi = S < 4 ? S * 3 + 3 : 6 + S * 2;
    if (S == 0 || c.always) {
#pragma unroll
      for (int i = lo; i < hi; i++) {
        pin(p[2 * i]); pin(p[2 * i + 1]);
        const float k = (i & 1) ? c.c1 : c.c0;
        const float t0 = p[2 * i] * k, t1 = p[2 * i + 1] * k;
        Sv[i] = pack_bf16(t0 * rcpf(1.f + ex2f(t0)), t1 * rcpf(1.f + ex2f(t1)));
        pin(Sv[i]);
      }
    }
  } else if constexpr (KIND == K_UP) {
    if (S < 4) {
#pragma unroll
      for (int i = 4 * S; i < 4 * S + 4; i++) {
        pin(p[2 * i]); pin(p[2 * i + 1]);
        Sv[i] = mul_bf16x2(Sv[i], pack_bf16(p[2 * i], p[2 * i + 1]));
      }
      sts128(c.priv + (n & 7) * 8192 + S * 512, &Sv[4 * S]);
    }
    if (S == 3 && n == 8) {
#pragma unroll
      for (int q = 30; q < 36; q++) lds128(&A[4 * q], c.priv + ((q >> 2) & 7) * 8192 + (q & 3) * 512);
    }
  } else {
    if (S < 2) {
      uint32_t v[8];
#pragma unroll
      for (int i = 0; i < 8; i++) {
        const int e = 16 * S + 2 * i;
        pin(p[e]); pin(p[e + 1]);
        v[i] = pack_bf16(p[e], p[e + 1]);
      }
      stg_relaxed(c.dst + S * 64, v);
      stg_relaxed(c.dst + S * 64 + 32, v + 4);
      if (n >= 3) {
        ldg_relaxed(&Sv[8 * S], c.src + S * 64);
        ldg_relaxed(&Sv[8 * S + 4], c.src + S * 64 + 32);
      }
    }
    if (S == 2) {
      c.dst = part_ptr(mt, (f + n) & 7, f) + frag_index();
      pinp(c.dst);
    }
    if (S == 4) {
      ensure_tile(Sv, c.src);
#pragma unroll
      for (int i = 0; i < 16; i++) { p[2 * i] = bf_lo(Sv[i]); p[2 * i + 1] = bf_hi(Sv[i]); pin(p[2 * i]); pin(p[2 * i + 1]); }
      c.src = (n < 7 ? part_ptr(mt, (f + n + 2) & 7, (f + 3) & 7) : part_ptr(mt, f, (f + 9 - n) & 7)) + frag_index();
      pinp(c.src);
      if (n == 8) load_tile(Sv, c.src);
    }
  }
}

template <int KIND, bool ODD, int S>
__device__ __forceinline__ void stage(Ctx& c, uint32_t (&A)[144], float (&d)[32], float (&p)[32], uint32_t (&Sv)[16], int n, int mt, int f) {
  if (!c.ready) mbar_wait(c.sb + bFull + S * 8, ODD);
  const uint32_t dlo = ((c.sb + oW) & 0x3FFFF) >> 4;
  constexpr int o = S * (kSlotBytes >> 4);
  wg_fence();
  wgmma64<S == 0 && KIND != K_XCHG, o>(d, &A[S * 24], dlo);
  wgmma64<false, o + 128>(d, &A[S * 24 + 4], dlo);
  wgmma64<false, o + 256>(d, &A[S * 24 + 8], dlo);
  wgmma64<false, o + 384>(d, &A[S * 24 + 12], dlo);
  wgmma64<false, o + 512>(d, &A[S * 24 + 16], dlo);
  wgmma64<false, o + 640>(d, &A[S * 24 + 20], dlo);
  wg_commit();
  if (KIND != K_FIRST || S > 0) {
    wg_wait<1>();
    if (c.rel) mbar_arrive_cluster(c.relbar + ((S + 5) % 6) * 8);
  }
  c.ready = mbar_probe(c.sb + bFull + ((S + 1) % 6) * 8, S == 5 ? !ODD : ODD);
  epi_slice<KIND, S>(c, A, p, Sv, n, mt, f);
}

template <int KIND, bool ODD>
__device__ __forceinline__ void pass(Ctx& c, uint32_t (&A)[144], float (&d)[32], float (&p)[32], uint32_t (&Sv)[16], int n, int mt, int f) {
  stage<KIND, ODD, 0>(c, A, d, p, Sv, n, mt, f);
  stage<KIND, ODD, 1>(c, A, d, p, Sv, n, mt, f);
  stage<KIND, ODD, 2>(c, A, d, p, Sv, n, mt, f);
  stage<KIND, ODD, 3>(c, A, d, p, Sv, n, mt, f);
  stage<KIND, ODD, 4>(c, A, d, p, Sv, n, mt, f);
  stage<KIND, ODD, 5>(c, A, d, p, Sv, n, mt, f);
}

__global__ void __cluster_dims__(2, 1, 1) __launch_bounds__(384, 1)
ffn_kernel(const __grid_constant__ CUtensorMap tmW1, const __grid_constant__ CUtensorMap tmW3,
           const __grid_constant__ CUtensorMap tmW2, const __grid_constant__ CUtensorMap tmH,
           __nv_bfloat16* __restrict__ out, int one, const char* w2) {
  extern __shared__ __align__(1024) unsigned char smem_raw[];
  const uint32_t sb = smem_u32(smem_raw);
  const int rank = blockIdx.x & 1, pr = blockIdx.x >> 1;
  const int mt = 2 * (pr & 7) + rank, f = pr >> 3;
  const int warp = __shfl_sync(0xffffffffu, threadIdx.x >> 5, 0), lane = threadIdx.x & 31;

  if (threadIdx.x == 0) {
    if (sb & 1023) __trap();
    for (int i = 0; i < 6; i++) { mbar_init(sb + bFull + i * 8, 1); mbar_init(sb + bEmpty + i * 8, 4); mbar_init(sb + bX + i * 8, 1); }
    mbar_init(sb + bGo, 1);
    mbar_init(sb + bP0, 32);
    asm volatile("fence.mbarrier_init.release.cluster;" ::: "memory");
  }
  __syncthreads();
  asm volatile("barrier.cluster.arrive.relaxed.aligned;\nbarrier.cluster.wait.aligned;" ::: "memory");

  if (warp >= 8) {
    asm volatile("setmaxnreg.dec.sync.aligned.u32 24;");
    if (warp <= 9) {
      if (lane == 0) {
        const int w = warp - 8;
#pragma unroll 1
        for (int p = 0; p < kPasses; p++) {
          const CUtensorMap* tm = p >= 18 ? &tmW2 : ((p & 1) ? &tmW3 : &tmW1);
          const int x = p >= 18 ? (p == 18 ? 8 : ((f + p - 18) & 7)) * 64 : f * 576 + (p >> 1) * 64;
          const int y = (p >= 18 ? f * 576 : 0) + rank * 48 + w * 96;
#pragma unroll
          for (int k = 0; k < 3; k++) {
            const uint32_t bo = (2 * k + w) * 8;
            if (p) mbar_wait(sb + bEmpty + bo, (p - 1) & 1);
            mbar_expect(sb + bFull + bo, kSlotBytes);
            tma2d_mc(sb + oW + (2 * k + w) * kSlotBytes + rank * 6144, tm, sb + bFull + bo, x, y + k * 192);
          }
        }
        for (int k = 0; k < 3; k++)
          if (2 * k + w < 5) mbar_wait(sb + bEmpty + (2 * k + w) * 8, 0);
      }
    } else {
      const int w = warp - 10;
      if (w == 0 && lane == 0) {
#pragma unroll
        for (int i = 0; i < 6; i++) mbar_expect(sb + bX + i * 8, 24576);
        asm volatile("griddepcontrol.wait;" ::: "memory");
        if (blockIdx.x == 0) g_lncnt = 0;
#pragma unroll
        for (int i = 0; i < 6; i++) tma2d(sb + oR + i * 24576, &tmH, sb + bX + i * 8, mt * 128 + (i / 3) * 64, (i % 3) * 192);
      }
      mbar_wait(sb + bX + 40, 0);
      {
        const uint32_t ones[4] = {kSentinel, kSentinel, kSentinel, kSentinel};
#pragma unroll 1
        for (int s = 0; s < NRESET; s++) {
          uint4* d8 = part_ptr(mt, 8, s) + f * 128 + w * 64 + lane;
          stg_relaxed(d8, ones);
          stg_relaxed(d8 + 32, ones);
          if (s != f) {
            uint4* dst = part_ptr(mt, f, s) + w * 512 + lane;
#pragma unroll 4
            for (int i = 0; i < 16; i++) stg_relaxed(dst + i * 32, ones);
          }
          __nanosleep(500);
        }
        __syncwarp();
        if (lane == 0) asm volatile("red.release.gpu.global.add.u32 [%0], 1;" ::"l"(&g_flag[mt * 32]) : "memory");
        if (w == 1 && lane == 0) {
          asm volatile("cp.async.bulk.prefetch.L2.global [%0], %1;" ::"l"(w2 + (size_t)(f * 16 + mt) * 41472), "r"(41472) : "memory");
        }
        if (w == 0 && lane == 0) {
          flag_wait(&g_flag[mt * 32], 16);
          mbar_arrive(sb + bGo);
        }
      }
      mbar_wait(sb + bP0, 0);
#pragma unroll 1
      for (int q = 2 * w; q < 2 * w + 2; q++) {
        const uint4* src = part_ptr(mt, 8, 0) + f * 128 + q * 32 + lane;
        float a[8] = {0.f, 0.f, 0.f, 0.f, 0.f, 0.f, 0.f, 0.f};
#pragma unroll 1
        for (int s = 0; s < 8; s += 2) {
          uint32_t v[8];
          ldg_relaxed(v, src);
          ldg_relaxed(v + 4, src + 1024);
          ensure_landed(v, src);
          ensure_landed(v + 4, src + 1024);
#pragma unroll
          for (int i = 0; i < 4; i++) { a[2 * i] += bf_lo(v[i]) + bf_lo(v[4 + i]); a[2 * i + 1] += bf_hi(v[i]) + bf_hi(v[4 + i]); }
          src += 2048;
        }
        {
          uint32_t v[4];
          float k0, k1;
          ldg_relaxed(v, src);
          asm volatile("ld.shared.v2.f32 {%0, %1}, [%2];" : "=f"(k0), "=f"(k1) : "r"(sb + oK + lane * 8) : "memory");
#pragma unroll
          for (int i = 0; i < 4; i++) {
            a[2 * i] = fmaf(a[2 * i], (i & 1) ? k1 : k0, bf_lo(v[i]));
            a[2 * i + 1] = fmaf(a[2 * i + 1], (i & 1) ? k1 : k0, bf_hi(v[i]));
          }
        }
        uint32_t* o = (uint32_t*)(out + (size_t)(mt * 128 + f * 16 + (lane >> 2)) * kD + 512 + q * 16 + (lane & 3) * 2);
        o[0] = pack_bf16(a[0], a[1]);
        o[4] = pack_bf16(a[4], a[5]);
        o[8 * kD / 2] = pack_bf16(a[2], a[3]);
        o[8 * kD / 2 + 4] = pack_bf16(a[6], a[7]);
      }
    }
  } else {
    asm volatile("setmaxnreg.inc.sync.aligned.u32 240;");
    const int wg = warp >> 2, tid = threadIdx.x & 127;
    Ctx c;
    c.sb = sb;
    c.rel = (tid & 0x5f) == 0;
    c.relbar = mapa(sb + bEmpty, warp & 1);
    c.priv = sb + oR + wg * kRWg + (warp & 3) * 2048 + lane * 16;
    pin(c.priv);
    c.ready = 0;
    c.always = one != 0;
    uint32_t A[144];
    float acc0[32], acc1[32];
    uint32_t Sv[16];
    {
      const uint32_t row = (lane >> 4) * 8 + (lane & 7);
      const uint32_t chunk = (2 * (warp & 3) + ((lane >> 3) & 1)) ^ wg ^ (lane & 7);
      const uint32_t base = sb + oR + wg * kRWg + row * 128 + chunk * 16;
      float s[8], q[8];
#pragma unroll
      for (int i = 0; i < 8; i++) s[i] = q[i] = 0.f;
#pragma unroll
      for (int g = 0; g < 3; g++) {
        mbar_wait(sb + bX + (wg * 3 + g) * 8, 0);
#pragma unroll
        for (int kk = 0; kk < 12; kk++) ldsm4t(&A[g * 48 + kk * 4], base + g * 24576 + kk * 2048);
#pragma unroll
        for (int i = 0; i < 48; i++) {
          const float lo = bf_lo(A[g * 48 + i]), hi = bf_hi(A[g * 48 + i]);
          s[i & 3] += lo; s[4 + (i & 3)] += hi;
          q[i & 3] = fmaf(lo, lo, q[i & 3]); q[4 + (i & 3)] = fmaf(hi, hi, q[4 + (i & 3)]);
        }
#pragma unroll
        for (int i = 0; i < 8; i++) { pin(s[i]); pin(q[i]); }
      }
      float s0 = (s[0] + s[2]) + (s[4] + s[6]), s1 = (s[1] + s[3]) + (s[5] + s[7]);
      float q0 = (q[0] + q[2]) + (q[4] + q[6]), q1 = (q[1] + q[3]) + (q[5] + q[7]);
#pragma unroll
      for (int m = 1; m <= 2; m++) {
        s0 += __shfl_xor_sync(0xffffffffu, s0, m); s1 += __shfl_xor_sync(0xffffffffu, s1, m);
        q0 += __shfl_xor_sync(0xffffffffu, q0, m); q1 += __shfl_xor_sync(0xffffffffu, q1, m);
      }
#pragma unroll
      for (int kk = 0; kk < 4; kk++) ldsm4t((uint32_t*)&acc1[kk * 4], base + f * 8192 + kk * 2048);
      if (warp == f) {
        uint4* dst = part_ptr(mt, 8, 8) + frag_index();
#pragma unroll
        for (int j = 0; j < 4; j++) stg128(dst + j * 32, &A[128 + j * 4]);
      }
      if (wg) asm volatile("bar.sync 2, 128;" ::: "memory"); else asm volatile("bar.sync 1, 128;" ::: "memory");
      const float m0 = s0 * (1.f / kD), m1 = s1 * (1.f / kD);
      Sv[0] = pack_bf16(m0, m0); Sv[1] = pack_bf16(m1, m1);
#pragma unroll
      for (int i = 0; i < 24; i++) { A[i] = sub_bf16x2(A[i], Sv[i & 1]); pin(A[i]); }
      const float v0 = fmaxf(q0 * (1.f / kD) - m0 * m0, 0.f), v1 = fmaxf(q1 * (1.f / kD) - m1 * m1, 0.f);
      float d0, d1;
      asm("sqrt.approx.f32 %0, %1;" : "=f"(d0) : "f"(round_bf16(round_bf16(v0) + 1e-5f)));
      asm("sqrt.approx.f32 %0, %1;" : "=f"(d1) : "f"(round_bf16(round_bf16(v1) + 1e-5f)));
      c.c0 = -1.4426950408889634f * rcpf(round_bf16(d0)); c.c1 = -1.4426950408889634f * rcpf(round_bf16(d1));
    }
    pass<K_FIRST, false>(c, A, acc0, acc1, Sv, 0, mt, f);
#pragma unroll 1
    for (int n = 0; n < 9; n++) {
      pass<K_GATE, true>(c, A, acc1, acc0, Sv, n, mt, f);
      pass<K_UP, false>(c, A, acc0, acc1, Sv, n, mt, f);
    }
    c.c0 *= 0.4804530139182014f; c.c1 *= 0.4804530139182014f;
    if (warp == f) asm volatile("st.shared.v2.f32 [%0], {%1, %2};" ::"r"(sb + oK + lane * 8), "f"(c.c0), "f"(c.c1) : "memory");
#pragma unroll
    for (int i = 0; i < 32; i++) acc1[i] = 0.f;
    c.src = nullptr;
#pragma unroll
    for (int i = 0; i < 16; i++) Sv[i] = 0;
    c.dst = part_ptr(mt, 8, f) + frag_index();
    mbar_wait(sb + bGo, 0);
#pragma unroll 1
    for (int n = 1; n < 9; n += 2) {
      pass<K_XCHG, true>(c, A, acc1, acc0, Sv, n, mt, f);
      if (n == 1 && warp == f) mbar_arrive(sb + bP0);
      pass<K_XCHG, false>(c, A, acc0, acc1, Sv, n + 1, mt, f);
    }
    {
      uint32_t hv[16];
#pragma unroll
      for (int q = 0; q < 4; q++) lds128(&hv[4 * q], c.priv + 8 * 8192 + q * 512);
      ensure_tile(Sv, c.src);
#pragma unroll
      for (int i = 0; i < 16; i++) {
        const float k = (i & 1) ? c.c1 : c.c0;
        acc1[2 * i] = fmaf(acc1[2 * i] + bf_lo(Sv[i]), k, bf_lo(hv[i]));
        acc1[2 * i + 1] = fmaf(acc1[2 * i + 1] + bf_hi(Sv[i]), k, bf_hi(hv[i]));
        pin(acc1[2 * i]); pin(acc1[2 * i + 1]);
      }
      wg_wait<0>();
#pragma unroll
      for (int i = 0; i < 32; i++) pin(acc0[i]);
      __syncwarp();
      const uint32_t stg = sb + oR + wg * kRWg + 2 * 8192 + (warp & 3) * 2048;
      const uint32_t ra = stg + (((lane >> 3) & 1) * 8 + (lane & 7)) * 128;
#pragma unroll
      for (int j = 0; j < 4; j++) {
        uint32_t v[4];
#pragma unroll
        for (int i = 0; i < 4; i++) {
          const int e = 8 * j + 2 * i;
          const float k = (i & 1) ? c.c1 : c.c0;
          v[i] = pack_bf16(fmaf(acc0[e], k, acc1[e]), fmaf(acc0[e + 1], k, acc1[e + 1]));
        }
        stsm4(ra + (((2 * j + (lane >> 4)) ^ (lane & 7)) << 4), v[0], v[1], v[2], v[3]);
      }
      __syncwarp();
#pragma unroll
      for (int i = 0; i < 4; i++) {
        const uint32_t rr = 4 * i + (lane >> 3);
        uint32_t v[4];
        lds128(v, stg + rr * 128 + (((lane & 7) ^ (rr & 7)) << 4));
        stg128(out + (size_t)(mt * 128 + warp * 16 + rr) * kD + f * 64 + (lane & 7) * 8, v);
      }
    }
  }
}

constexpr int kSsmThreads = 640;
constexpr uint32_t kUxPad = 512, kUxCh = kUxPad + 8192;
constexpr uint32_t kKeWords = 16 + 544, kCWords = 96;
constexpr uint32_t kTabCh = (kKeWords + 2 * kCWords + 656) * 4;
constexpr uint32_t kFacRow = 144, kFacWarp = 53 * kFacRow;
constexpr uint32_t kQ4Pad = 64, kQ4Words = kQ4Pad + 1568, kQ8Pad = 128, kQ8Words = kQ8Pad + 1024;
constexpr uint32_t kQCh = (kQ4Words + kQ8Words) * 4;
constexpr uint32_t kLnRow = 1168;
constexpr uint32_t aUx = 0, aTab = aUx + 5 * kUxCh, aFac = aTab + 5 * kTabCh, aBar = aFac + 20 * kFacWarp + 512, aEnd = aBar + 16;
constexpr uint32_t aQ = aFac, aOut = aQ + 5 * kQCh;
constexpr int kSsmSmem = aEnd;
static_assert(aOut + 20 * 2048 <= aBar, "smem");
static_assert(2 * 16 * kLnRow <= 5 * kUxCh, "smem");
static_assert(aTab % 128 == 0 && aFac % 128 == 0 && kQCh % 128 == 0 && kSsmSmem <= 232448, "smem");

struct Cx { float r, i; };
__device__ __forceinline__ Cx cmul(Cx a, Cx b) { return {fmaf(a.r, b.r, -a.i * b.i), fmaf(a.r, b.i, a.i * b.r)}; }
__device__ __forceinline__ Cx cexp_scaled(float lr, float turns, float e) {
  const float t = turns * e, fr = (t - rintf(t)) * 6.283185307179586f, m = ex2f(lr * e);
  return {m * __cosf(fr), m * __sinf(fr)};
}
__device__ __forceinline__ void sts32(uint32_t a, uint32_t v) { asm volatile("st.shared.u32 [%0], %1;" ::"r"(a), "r"(v) : "memory"); }
__device__ __forceinline__ uint32_t lds32(uint32_t a) { uint32_t v; asm volatile("ld.shared.u32 %0, [%1];" : "=r"(v) : "r"(a) : "memory"); return v; }
__device__ __forceinline__ float ldsf(uint32_t a) { return __uint_as_float(lds32(a)); }
__device__ __forceinline__ void ldsm4(uint32_t* r, uint32_t a) {
  asm volatile("ldmatrix.sync.aligned.m8n8.x4.shared.b16 {%0,%1,%2,%3}, [%4];"
               : "=r"(r[0]), "=r"(r[1]), "=r"(r[2]), "=r"(r[3]) : "r"(a) : "memory");
}
__device__ __forceinline__ void stsm4t(uint32_t a, uint32_t r0, uint32_t r1, uint32_t r2, uint32_t r3) {
  asm volatile("stmatrix.sync.aligned.m8n8.x4.trans.shared.b16 [%0], {%1,%2,%3,%4};" ::"r"(a), "r"(r0), "r"(r1), "r"(r2), "r"(r3) : "memory");
}
__device__ __forceinline__ void mma16816(float* d, uint32_t a0, uint32_t a1, uint32_t a2, uint32_t a3, uint32_t b0, uint32_t b1) {
  asm volatile("mma.sync.aligned.m16n8k16.row.col.f32.bf16.bf16.f32 {%0,%1,%2,%3}, {%4,%5,%6,%7}, {%8,%9}, {%0,%1,%2,%3};"
               : "+f"(d[0]), "+f"(d[1]), "+f"(d[2]), "+f"(d[3]) : "r"(a0), "r"(a1), "r"(a2), "r"(a3), "r"(b0), "r"(b1));
}
__device__ __forceinline__ void bar_sync(int id, int n) { asm volatile("bar.sync %0, %1;" ::"r"(id), "r"(n) : "memory"); }
__device__ __forceinline__ void bar_arrive(int id, int n) { asm volatile("bar.arrive %0, %1;" ::"r"(id), "r"(n) : "memory"); }
__device__ __forceinline__ uint32_t ux_swz(int blk) { return (blk & 2) | ((blk >> 2) & 1); }
__device__ __forceinline__ int kv_index(int lag) { return lag < 256 ? lag : 128 + ((lag + ((lag >> 1) & 1)) >> 1); }

template <bool HI>
__device__ __forceinline__ void conv_unit(uint32_t sb, int slot, int ch, int warp, int lane, float dskip) {
  constexpr int O0 = HI ? 8 : 0;
  const int g = lane >> 2, t = lane & 3;
  const uint32_t ux = sb + aUx + slot * kUxCh + kUxPad;
  const uint32_t tab = sb + aTab + slot * kTabCh;
  float acc[8][4];
#pragma unroll
  for (int o = 0; o < 8; o++) acc[o][0] = acc[o][1] = acc[o][2] = acc[o][3] = 0.f;

  const uint32_t ke = tab + (16 + g - 2 * t) * 4;
  uint32_t am[4];
#pragma unroll
  for (int q = 0; q < 4; q++) am[q] = lds32(ke + (128 * q - 8) * 4);
  const uint32_t nk = pack_bf16(-ldsf(tab + (kKeWords + 2 * kCWords + 512) * 4), 0.f);
#pragma unroll 1
  for (int rho = 0; rho < 8; rho++) {
    constexpr int X0 = HI ? 4 : 0, NX = HI ? 12 : 8;
    const int rb = (lane & 7) - rho;
    const uint32_t ga = ux + (rb + (lane >> 4) * 8) * 64 + ((((lane >> 3) & 1) ^ ux_swz(rb)) << 4);
    uint32_t G[NX][2], a0[4], a1[4];
#pragma unroll
    for (int x = NX - 2; x >= 0; x -= 2) ldsm4(&G[x][0], ga + (X0 + x) * 512);
#pragma unroll
    for (int q = 0; q < 4; q++) { a0[q] = lds32(ke + (128 * q + 16 * rho) * 4); a1[q] = lds32(ke + (128 * q + 16 * rho + 8) * 4); }
#pragma unroll
    for (int q = 0; q < 4; q++)
#pragma unroll
      for (int o = 7; o >= 0; o--)
        if (O0 + o - q >= 0) mma16816(acc[o], a0[q], a1[q], am[q], a0[q], G[O0 + o - q - X0][0], G[O0 + o - q - X0][1]);
    if (rho == 0) {
      const uint32_t b0 = lds32(ke + 512 * 4), bm = lds32(ke + 504 * 4);
#pragma unroll
      for (int o = 7; o >= 0; o--)
        if (O0 + o - 4 >= 0) mma16816(acc[o], b0, 0u, bm, b0, G[O0 + o - 4 - X0][0], G[O0 + o - 4 - X0][1]);
    }
    if (rho == 7 || (HI && rho == 0)) {
      const int d = g - 2 * t;
      const uint32_t wp = (d == 4 || d == 5 ? nk : 0u) | (d == 5 || d == 6 ? nk << 16 : 0u);
      const uint32_t wn = (d == -4 || d == -3 ? nk : 0u) | (d == -3 || d == -2 ? nk << 16 : 0u);
      if (HI) {
        const uint32_t f0 = rho ? 0u : wn, f1 = rho ? wp : 0u, f2 = rho ? 0u : wp;
        uint32_t F[8][2];
#pragma unroll
        for (int x = 0; x < 8; x += 2) ldsm4(&F[x][0], ga + (x + (rho ? 1 : 0)) * 512);
#pragma unroll
        for (int o = 0; o < 8; o++) mma16816(acc[o], f0, f1, f2, f0, F[o][0], F[o][1]);
      } else {
        mma16816(acc[7], 0u, wp, 0u, 0u, G[0][0], G[0][1]);
      }
    }
#pragma unroll
    for (int q = 0; q < 4; q++) am[q] = a1[q];
  }

  bar_sync(7, kSsmThreads);
  {
    const uint32_t q4 = sb + aQ + slot * kQCh + kQ4Pad * 4;
    uint32_t off[4], B[10][2];
#pragma unroll
    for (int i = 0; i < 4; i++) {
      const int w = g - 8 * t + (i & 1) * 8 - (i >> 1) * 32;
      off[i] = q4 + (w ^ ((w >> 3) & 4)) * 4;
    }
    const uint32_t cb = tab + (kKeWords + 2 * g + t) * 4;
#pragma unroll
    for (int ks = 0; ks < (HI ? 10 : 9); ks++) { B[ks][0] = lds32(cb + ks * 32); B[ks][1] = lds32(cb + ks * 32 + 16); }
#pragma unroll
    for (int tau = (HI ? 1 : 0); tau <= (HI ? 24 : 8); tau++) {
      uint32_t a[4];
#pragma unroll
      for (int i = 0; i < 4; i++) a[i] = lds32(off[i] + tau * 256);
#pragma unroll
      for (int o = 0; o < 8; o++) {
        const int ks = 2 * (O0 + o) - 6 - tau;
        if (ks >= 0 && ks < 10) mma16816(acc[o], a[0], a[1], a[2], a[3], B[ks][0], B[ks][1]);
      }
    }
  }
  {
    const uint32_t q8 = sb + aQ + slot * kQCh + (kQ4Words + kQ8Pad) * 4;
    uint32_t off[4], B[9][2];
#pragma unroll
    for (int i = 0; i < 4; i++) {
      const int w = g - 16 - 16 * t + (i & 1) * 8 - (i >> 1) * 64;
      off[i] = q8 + (w ^ (((w >> 5) & 1) * 12)) * 4;
    }
    const uint32_t cb = tab + (kKeWords + kCWords + g + t) * 4;
#pragma unroll
    for (int ks = 0; ks < (HI ? 9 : 1); ks++) { B[ks][0] = lds32(cb + ks * 32); B[ks][1] = lds32(cb + ks * 32 + 16); }
#pragma unroll
    for (int tau = 0; tau <= (HI ? 8 : 0); tau++) {
      uint32_t a[4];
#pragma unroll
      for (int i = 0; i < 4; i++) a[i] = lds32(off[i] + tau * 512);
#pragma unroll
      for (int o = 0; o < 8; o++) {
        const int ks = O0 + o - 7 - tau;
        if (ks >= 0 && ks < 9) mma16816(acc[o], a[0], a[1], a[2], a[3], B[ks][0], B[ks][1]);
      }
    }
  }

  const uint32_t stg = sb + aOut + warp * 2048;
  const uint32_t ea = ux + (lane & 7) * 64 + (((lane >> 3) ^ ux_swz(lane & 7)) << 4);
  const uint32_t sa = stg + (lane >> 4) * 256 + (lane & 7) * 32 + ((((lane >> 3) ^ (lane >> 2)) & 1) << 4);
#pragma unroll
  for (int o = 0; o < 8; o += 2) {
    uint32_t r[4];
#pragma unroll
    for (int k = 0; k < 2; k++) {
      uint32_t v[4];
      ldsm4t(v, ea + (O0 + o + k) * 512);
      const float* a = acc[o + k];
      r[2 * k] = pack_bf16(fmaf(dskip, bf_lo(v[0]), a[0]) + bf_lo(v[2]), fmaf(dskip, bf_hi(v[0]), a[1]) + bf_hi(v[2]));
      r[2 * k + 1] = pack_bf16(fmaf(dskip, bf_lo(v[1]), a[2]) + bf_lo(v[3]), fmaf(dskip, bf_hi(v[1]), a[3]) + bf_hi(v[3]));
    }
    stsm4t(sa + o * 256, r[0], r[1], r[2], r[3]);
  }
  __syncwarp();
  uint4* dst = (uint4*)(g_hT + (size_t)ch * kL + O0 * 128) + lane;
#pragma unroll
  for (int i = 0; i < 4; i++) {
    uint32_t v[4];
    lds128(v, stg + i * 512 + lane * 16);
    stg128(dst + i * 32, v);
  }
}

template <bool BOTH>
__device__ __forceinline__ void box_job(uint32_t sb, int slot, int c) {
  const uint32_t ux = sb + aUx + slot * kUxCh + kUxPad;
  uint32_t v[16];
#pragma unroll
  for (int k = BOTH ? 0 : 1; k < 4; k++) {
    const int cc = c - 2 + k, blk = cc >> 1;
    lds128(&v[4 * k], ux + blk * 64 + (((cc & 1) ^ ux_swz(blk)) << 4));
  }
  constexpr int lo = BOTH ? 5 : 11, hi = BOTH ? 28 : 26;
  float P[29];
  P[lo] = 0.f;
#pragma unroll
  for (int k = lo; k < hi; k++) P[k + 1] = P[k] + ((k & 1) ? bf_hi(v[k >> 1]) : bf_lo(v[k >> 1]));
  const uint32_t odd = (c >> 2) & 1;
  uint32_t w[8];
#pragma unroll
  for (int i = 0; i < 8; i++) w[i] = pack_bf16(P[16 + i + 3] - P[16 + i - 2], P[16 + i - 2] - P[16 + i - 5]);
  const uint32_t q4 = sb + aQ + slot * kQCh + kQ4Pad * 4 + c * 32;
  sts128(q4 + (odd << 4), w);
  sts128(q4 + ((odd ^ 1) << 4), w + 4);
  if (BOTH) {
#pragma unroll
    for (int i = 0; i < 8; i++) w[i] = pack_bf16(P[16 + i + 5] - P[16 + i - 4], P[16 + i - 4] - P[16 + i - 11]);
    const uint32_t q8 = sb + aQ + slot * kQCh + (kQ4Words + kQ8Pad) * 4 + (c ^ odd) * 32;
    sts128(q8 + (odd << 4), w);
    sts128(q8 + ((odd ^ 1) << 4), w + 4);
  }
}

struct SsmArgs {
  const __nv_bfloat16 *x, *are, *aim, *bre, *bim, *cre, *cim, *ldt, *dsk;
  const char *w1, *w3;
};

__global__ void __launch_bounds__(kSsmThreads, 1) ssm_kernel(const SsmArgs a) {
  extern __shared__ __align__(1024) unsigned char smem_raw[];
  const uint32_t sb = smem_u32(smem_raw);
  const int b = blockIdx.x, tid = threadIdx.x;
  const int warp = __shfl_sync(0xffffffffu, tid >> 5, 0), lane = tid & 31;
  asm volatile("griddepcontrol.launch_dependents;");

  uint32_t xv[9];
  if (warp < 16) {
    const uint32_t* xr = (const uint32_t*)(a.x + (size_t)(b * 16 + warp) * kD) + lane;
#pragma unroll
    for (int i = 0; i < 9; i++) xv[i] = __ldg(xr + i * 32);
  }
  const int slot = warp >> 2;
  const int ch = slot < 4 ? 4 * b + slot : 512 + (b >> 1);
  const int pi = ch * kN + (warp & 3) * 32 + lane;
  const float are = __bfloat162float(a.are[pi]), aim = __bfloat162float(a.aim[pi]);
  const float bre = __bfloat162float(a.bre[pi]), bim = __bfloat162float(a.bim[pi]);
  const float cre = __bfloat162float(a.cre[pi]), cim = __bfloat162float(a.cim[pi]);
  const float ldt = __bfloat162float(a.ldt[ch]);
  if (tid == 0) {
    mbar_init(sb + aBar, 1);
    asm volatile("fence.mbarrier_init.release.cluster;" ::: "memory");
  }
  if (b < 16 && tid == 32) g_flag[b * 32] = 0;

  if (warp < 16) {
    float s = 0.f;
#pragma unroll
    for (int i = 0; i < 9; i++) s += bf_lo(xv[i]) + bf_hi(xv[i]);
#pragma unroll
    for (int m = 16; m; m >>= 1) s += __shfl_xor_sync(0xffffffffu, s, m);
    const float mean = s * (1.f / kD);
    float q = 0.f;
#pragma unroll
    for (int i = 0; i < 9; i++) {
      const float lo = bf_lo(xv[i]) - mean, hi = bf_hi(xv[i]) - mean;
      q = fmaf(lo, lo, fmaf(hi, hi, q));
    }
#pragma unroll
    for (int m = 16; m; m >>= 1) q += __shfl_xor_sync(0xffffffffu, q, m);
    float sd;
    asm("sqrt.approx.f32 %0, %1;" : "=f"(sd) : "f"(round_bf16(round_bf16(q * (1.f / kD)) + 1e-5f)));
    const float r = rcpf(round_bf16(sd));
    const uint32_t mm = pack_bf16(mean, mean);
    const uint32_t ra = sb + aUx + warp * kLnRow + lane * 4;
#pragma unroll
    for (int i = 0; i < 9; i++) {
      const uint32_t d = sub_bf16x2(xv[i], mm);
      sts32(ra + i * 128, pack_bf16(bf_lo(d) * r, bf_hi(d) * r));
      sts32(ra + 16 * kLnRow + i * 128, xv[i]);
    }
  }
  __syncthreads();
  {
    const int i = lane & 7, j = lane >> 3;
    const uint32_t la = sb + aUx + ((i >> 2) * 16 + ((i >> 1) & 1) * 8 + 2 * j + (i & 1)) * kLnRow;
    uint4* dst = g_ux + ((lane >> 2) * 128 + b) * 4 + ((lane & 3) ^ ux_swz(b));
    for (int cg = warp; cg < 72; cg += 20) {
      uint32_t v[4];
      ldsm4t(v, la + cg * 16);
      stg128(dst + cg * 4096, v);
    }
  }
  __syncthreads();
  if (tid == kSsmThreads - 32) asm volatile("red.release.gpu.global.add.u32 [%0], 1;" ::"l"(&g_lncnt) : "memory");
  if (tid < 2) {
    const char* p = (tid ? a.w3 : a.w1) + (size_t)b * 41472;
    asm volatile("cp.async.bulk.prefetch.L2.global [%0], %1;" ::"l"(p), "r"(41472) : "memory");
  }
  if (tid >= 64 && tid < 64 + 160) {
    const uint32_t z[4] = {0, 0, 0, 0};
    sts128(sb + aUx + ((tid - 64) >> 5) * kUxCh + lane * 16, z);
  }

  const uint32_t fac = sb + aFac + warp * kFacWarp;
  {
    const float dt = round_bf16(expf(ldt));
    const float lr = dt * are * 1.4426950408889634f, turns = dt * aim * 0.15915494309189535f;
    const uint32_t fa = fac + lane * 4;
    {
      const Cx z8 = cexp_scaled(lr, turns, 8.f);
      Cx R[4];
      R[0] = {1.f, 0.f}; R[1] = z8; R[2] = cmul(z8, z8); R[3] = cmul(R[2], z8);
      const Cx z32 = cmul(R[2], R[2]);
#pragma unroll
      for (int j = 0; j < 32; j++) {
        sts32(fa + j * kFacRow, pack_bf16(R[j & 3].r, R[j & 3].i));
        if (j < 28) R[j & 3] = j == 0 ? z32 : cmul(R[j & 3], z32);
      }
    }
    {
      const Cx z1 = cexp_scaled(lr, -turns, 1.f), z256 = cexp_scaled(lr, -turns, 256.f);
      const Cx z2 = cmul(z1, z1), z4 = cmul(z2, z2);
      Cx Lv[21];
      Lv[0] = cmul({cre, -cim}, {dt * bre, -dt * bim});
      Lv[1] = cmul(Lv[0], z1); Lv[2] = cmul(Lv[0], z2); Lv[3] = cmul(Lv[1], z2);
#pragma unroll
      for (int m = 4; m < 8; m++) Lv[m] = cmul(Lv[m - 4], z4);
#pragma unroll
      for (int m = 8; m < 12; m++) Lv[m] = cmul(Lv[2 * (m - 8)], z256);
      Lv[12] = cmul(Lv[8], z256); Lv[13] = cmul(Lv[10], z256);
      Lv[14] = cmul(Lv[12], z256); Lv[15] = cmul(Lv[13], z256);
      Lv[16] = cmul(Lv[14], z256);
#pragma unroll
      for (int m = 17; m < 21; m++) Lv[m] = cmul(Lv[m - 1], z256);
#pragma unroll
      for (int m = 0; m < 21; m++) sts32(fa + (32 + m) * kFacRow, pack_bf16(Lv[m].r, Lv[m].i));
    }
  }
  __syncwarp();
  {
    float c[6][4];
#pragma unroll
    for (int i = 0; i < 6; i++) c[i][0] = c[i][1] = c[i][2] = c[i][3] = 0.f;
    uint32_t B[3][8];
    const uint32_t ba = fac + (32 + (lane & 7)) * kFacRow + (lane >> 3) * 16;
#pragma unroll
    for (int n = 0; n < 3; n++) { ldsm4(&B[n][0], ba + n * 8 * kFacRow); ldsm4(&B[n][4], ba + n * 8 * kFacRow + 64); }
    const uint32_t aa = fac + (lane & 15) * kFacRow + (lane >> 4) * 16;
#pragma unroll
    for (int ks = 0; ks < 4; ks++)
#pragma unroll
      for (int m = 0; m < 2; m++) {
        uint32_t av[4];
        ldsm4(av, aa + m * 16 * kFacRow + ks * 32);
#pragma unroll
        for (int n = 0; n < 3; n++) mma16816(c[m * 3 + n], av[0], av[1], av[2], av[3], B[n][2 * ks], B[n][2 * ks + 1]);
      }
    __syncwarp();
#pragma unroll
    for (int p = 0; p < 12; p++)
      asm volatile("st.shared.v2.f32 [%0], {%1, %2};" ::"r"(fac + 1024 + p * 256 + lane * 8), "f"(c[p >> 1][(p & 1) * 2]), "f"(c[p >> 1][(p & 1) * 2 + 1]) : "memory");
  }
  bar_sync(1 + slot, 128);
  const uint32_t tab = sb + aTab + slot * kTabCh, kv = tab + (kKeWords + 2 * kCWords) * 4;
  {
#pragma unroll
    for (int k = 0; k < 3; k++) {
      const int p = (warp & 3) * 3 + k, tile = p >> 1;
      float s0 = 0.f, s1 = 0.f;
#pragma unroll
      for (int w = 0; w < 4; w++) {
        float u0, u1;
        asm volatile("ld.shared.v2.f32 {%0, %1}, [%2];" : "=f"(u0), "=f"(u1) : "r"(sb + aFac + (slot * 4 + w) * kFacWarp + 1024 + p * 256 + lane * 8) : "memory");
        s0 += u0; s1 += u1;
      }
      const int j = (tile / 3) * 16 + (p & 1) * 8 + (lane >> 2), n = tile % 3, t = lane & 3;
      int i0, i1;
      if (n == 0) { i0 = 2 * t + 8 * j; i1 = i0 + 1; }
      else if (n == 1) { i0 = t < 2 ? 256 + 2 * t + 4 * j : 384 + 64 * (t - 2) + 2 * j; i1 = i0 + 1; }
      else { i0 = 512 + 64 * t + j; i1 = i0 + 32; }
      if (i0 <= 640) sts32(kv + i0 * 4, __float_as_uint(s0));
      if (i1 <= 640) sts32(kv + i1 * 4, __float_as_uint(s1));
    }
  }
  bar_sync(1 + slot, 128);
  {
    const int i = tid & 127;
    float d[5];
#pragma unroll
    for (int k = 0; k < 5; k++) d[k] = ldsf(kv + kv_index(max(4 * i - 1 + k, 0)) * 4);
    if (i == 0) d[0] = 0.f;
    if (i == 127) { d[3] -= d[4]; d[4] = 0.f; }
    uint32_t w[4];
#pragma unroll
    for (int k = 0; k < 4; k++) w[k] = pack_bf16(d[k + 1], d[k]);
    sts128(tab + (16 + 4 * i) * 4, w);
    if (i < 48) sts32(tab + (i < 16 ? i : 512 + i) * 4, 0);
    if (i < 96) {
      const int k4 = i - 16, k8 = i - 7;
      sts32(tab + (kKeWords + i) * 4, k4 >= 0 && k4 < 64 ? pack_bf16(ldsf(kv + (384 + 2 * k4) * 4), ldsf(kv + (385 + 2 * k4) * 4)) : 0u);
      sts32(tab + (kKeWords + kCWords + i) * 4,
            k8 >= 0 && k8 <= 64 ? pack_bf16(ldsf(kv + (512 + 2 * k8) * 4), k8 < 64 ? ldsf(kv + (513 + 2 * k8) * 4) : 0.f) : 0u);
    }
  }
  if (tid == kSsmThreads - 32) {
    mbar_expect(sb + aBar, 5 * 8192);
    flag_wait(&g_lncnt, 128);
    asm volatile("fence.proxy.async;" ::: "memory");
#pragma unroll
    for (int s = 0; s < 5; s++)
      bulk_g2s(sb + aUx + s * kUxCh + kUxPad, g_ux + (size_t)(s < 4 ? 4 * b + s : 512 + (b >> 1)) * 512, 8192, sb + aBar);
  }
  __syncthreads();
  mbar_wait(sb + aBar, 0);

  const unsigned long long map = (b & 1) ? 0x4fff31092ba8ull : 0x3fff20b91ca8ull;
  const int code = warp < 12 ? (int)((map >> (4 * warp)) & 15) : 15;
  if (code == 15) {
    const int ht = (warp < 11 ? warp - 8 : warp - 9) * 32 + lane;
    for (int z = ht; z < 5 * 52; z += 352) {
      const int s = z / 52, k = z % 52;
      const uint32_t zz[4] = {0, 0, 0, 0};
      const int w4 = k < 14 ? 4 * k : kQ4Pad + 1536 + 4 * (k - 14);
      const int w8 = 4 * (k - 22);
      sts128(sb + aQ + s * kQCh + (k < 22 ? w4 : kQ4Words + (w8 ^ (((w8 >> 5) & 1) * 12))) * 4, zz);
    }
    for (int job = ht; job < 5 * 129; job += 352) box_job<true>(sb, job / 129, job % 129 - 1);
    if (ht < 320) box_job<false>(sb, ht >> 6, 128 + (ht & 63));
    bar_arrive(7, kSsmThreads);
  } else {
    const int s = code & 7, c = s < 4 ? 4 * b + s : 512 + (b >> 1);
    const float dskip = __bfloat162float(a.dsk[c]);
    if (code & 8) conv_unit<true>(sb, s, c, warp, lane, dskip);
    else conv_unit<false>(sb, s, c, warp, lane, dskip);
  }
}

typedef CUresult (*EncodeFn)(CUtensorMap*, CUtensorMapDataType, cuuint32_t, void*, const cuuint64_t*, const cuuint64_t*,
                             const cuuint32_t*, const cuuint32_t*, CUtensorMapInterleave, CUtensorMapSwizzle,
                             CUtensorMapL2promotion, CUtensorMapFloatOOBfill);

void encode2d(EncodeFn fn, CUtensorMap* tm, void* p, int cols, int rows, int bx, int by) {
  cuuint64_t gd[2] = {(cuuint64_t)cols, (cuuint64_t)rows}, gs[1] = {(cuuint64_t)cols * 2};
  cuuint32_t box[2] = {(cuuint32_t)bx, (cuuint32_t)by}, es[2] = {1, 1};
  fn(tm, CU_TENSOR_MAP_DATA_TYPE_BFLOAT16, 2, p, gd, gs, box, es, CU_TENSOR_MAP_INTERLEAVE_NONE, CU_TENSOR_MAP_SWIZZLE_128B,
     CU_TENSOR_MAP_L2_PROMOTION_L2_128B, CU_TENSOR_MAP_FLOAT_OOB_FILL_NONE);
}

}

extern "C" void kernel_launch(void* const* d_in, const int* in_sizes, int n_in, void* d_out, int out_size) {
  typedef const __nv_bfloat16* P;
  void* fn = nullptr;
  cudaDriverEntryPointQueryResult qr;
  cudaGetDriverEntryPoint("cuTensorMapEncodeTiled", &fn, cudaEnableDefault, &qr);
  void* hT;
  cudaGetSymbolAddress(&hT, g_hT);
  CUtensorMap t1, t3, t2, th;
  encode2d((EncodeFn)fn, &t1, d_in[10], kF, kD, 64, 48);
  encode2d((EncodeFn)fn, &t3, d_in[11], kF, kD, 64, 48);
  encode2d((EncodeFn)fn, &t2, d_in[12], kD, kF, 64, 48);
  encode2d((EncodeFn)fn, &th, hT, kL, kD, 64, 192);
  cudaFuncSetAttribute(ffn_kernel, cudaFuncAttributeMaxDynamicSharedMemorySize, kFfnSmem);

  cudaFuncSetAttribute(ssm_kernel, cudaFuncAttributeMaxDynamicSharedMemorySize, kSsmSmem);
  SsmArgs sa = {(P)d_in[0], (P)d_in[1], (P)d_in[2], (P)d_in[3], (P)d_in[4], (P)d_in[5], (P)d_in[6], (P)d_in[7], (P)d_in[8],
                (const char*)d_in[10], (const char*)d_in[11]};
  ssm_kernel<<<128, kSsmThreads, kSsmSmem, cudaStreamPerThread>>>(sa);

  cudaLaunchConfig_t cfg = {};
  cfg.gridDim = dim3(128);
  cfg.blockDim = dim3(384);
  cfg.dynamicSmemBytes = kFfnSmem;
  cfg.stream = cudaStreamPerThread;
  cudaLaunchAttribute at[1];
  at[0].id = cudaLaunchAttributeProgrammaticStreamSerialization;
  at[0].val.programmaticStreamSerializationAllowed = 1;
  cfg.attrs = at;
  cfg.numAttrs = 1;
  cudaLaunchKernelEx(&cfg, ffn_kernel, t1, t3, t2, th, (__nv_bfloat16*)d_out, 1, (const char*)d_in[12]);
}
```

```cpp
#include <cuda_runtime.h>
#include <cuda_bf16.h>
#include <cuda.h>
#include <stdint.h>
#include <string.h>

namespace {

constexpr int kL = 2048, kD = 576, kF = 4608, kN = 128;

}

__device__ __align__(1024) __nv_bfloat16 g_hT[kD * kL];
__device__ uint4 g_part[16 * 9 * 9 * 1024];
__device__ unsigned g_epoch;
__device__ uint4 g_uT[kD * 256];
__device__ uint4 g_xT[kD * 256];
#define NREP 1
#define BACKOFF 0
__device__ unsigned g_lncnt[2 * 32 * 64];

namespace {

__device__ __forceinline__ uint32_t smem_u32(const void* p) { return (uint32_t)__cvta_generic_to_shared(p); }
__device__ __forceinline__ void mbar_init(uint32_t b, int c) {
  asm volatile("mbarrier.init.shared::cta.b64 [%0], %1;" ::"r"(b), "r"(c));
}
__device__ __forceinline__ void mbar_expect(uint32_t b, int bytes) {
  asm volatile("mbarrier.arrive.expect_tx.shared::cta.b64 _, [%0], %1;" ::"r"(b), "r"(bytes) : "memory");
}
__device__ __forceinline__ void mbar_arrive(uint32_t b) {
  asm volatile("mbarrier.arrive.shared::cta.b64 _, [%0];" ::"r"(b) : "memory");
}
__device__ __forceinline__ void mbar_arrive_cluster(uint32_t b) {
  asm volatile("mbarrier.arrive.shared::cluster.b64 _, [%0];" ::"r"(b) : "memory");
}
__device__ __forceinline__ bool elect_one() {
  uint32_t p;
  asm volatile("{\n.reg .pred q;\nelect.sync _|q, 0xffffffff;\nselp.u32 %0, 1, 0, q;\n}\n" : "=r"(p));
  return p;
}
__device__ __forceinline__ uint32_t mapa(uint32_t a, uint32_t rank) {
  uint32_t r;
  asm volatile("mapa.shared::cluster.u32 %0, %1, %2;" : "=r"(r) : "r"(a), "r"(rank));
  return r;
}
__device__ __forceinline__ void mbar_wait(uint32_t b, uint32_t parity) {
  asm volatile(
      "{\n.reg .pred p;\n.reg .u32 n;\n"
      "mbarrier.try_wait.parity.shared::cta.b64 p, [%0], %1;\n"
      "@p bra DONE;\n"
      "mov.u32 n, 0;\n"
      "LOOP:\n"
      "mbarrier.try_wait.parity.shared::cta.b64 p, [%0], %1;\n"
      "@p bra DONE;\n"
      "add.u32 n, n, 1;\n"
      "setp.lt.u32 p, n, 4000000;\n"
      "@p bra LOOP;\n"
      "trap;\n"
      "DONE:\n}\n" ::"r"(b), "r"(parity) : "memory");
}
__device__ __forceinline__ void flag_wait(const unsigned* p, unsigned target) {
  unsigned v;
#pragma unroll 1
  for (int it = 0; it < 4000000; it++) {
    asm volatile("ld.acquire.gpu.global.u32 %0, [%1];" : "=r"(v) : "l"(p) : "memory");
    if (v >= target) return;
    if (BACKOFF) __nanosleep(BACKOFF);
  }
  asm volatile("trap;");
}
__device__ __forceinline__ void tma2d_mc(uint32_t dst, const CUtensorMap* tm, uint32_t bar, int x, int y) {
  asm volatile("cp.async.bulk.tensor.2d.shared::cluster.global.mbarrier::complete_tx::bytes.multicast::cluster [%0], [%1, {%3, %4}], [%2], %5;"
               ::"r"(dst), "l"(tm), "r"(bar), "r"(x), "r"(y), "h"((uint16_t)3) : "memory");
}
__device__ __forceinline__ void tma_prefetch(const CUtensorMap* tm, int x, int y) {
  asm volatile("cp.async.bulk.prefetch.tensor.2d.L2.global [%0, {%1, %2}];" ::"l"(tm), "r"(x), "r"(y) : "memory");
}
__device__ __forceinline__ void bulk_g2s(uint32_t dst, const void* src, int bytes, uint32_t bar) {
  asm volatile("cp.async.bulk.shared::cluster.global.mbarrier::complete_tx::bytes [%0], [%1], %2, [%3];"
               ::"r"(dst), "l"(src), "r"(bytes), "r"(bar) : "memory");
}
__device__ __forceinline__ void ldsm4t(uint32_t* r, uint32_t a) {
  asm volatile("ldmatrix.sync.aligned.m8n8.x4.trans.shared.b16 {%0,%1,%2,%3}, [%4];"
               : "=r"(r[0]), "=r"(r[1]), "=r"(r[2]), "=r"(r[3]) : "r"(a) : "memory");
}
__device__ __forceinline__ void stsm4(uint32_t a, uint32_t r0, uint32_t r1, uint32_t r2, uint32_t r3) {
  asm volatile("stmatrix.sync.aligned.m8n8.x4.shared.b16 [%0], {%1,%2,%3,%4};" ::"r"(a), "r"(r0), "r"(r1), "r"(r2), "r"(r3) : "memory");
}
__device__ __forceinline__ void lds128(uint32_t* r, uint32_t a) {
  asm volatile("ld.shared.v4.u32 {%0,%1,%2,%3}, [%4];" : "=r"(r[0]), "=r"(r[1]), "=r"(r[2]), "=r"(r[3]) : "r"(a) : "memory");
}
__device__ __forceinline__ void sts128(uint32_t a, const uint32_t* r) {
  asm volatile("st.shared.v4.u32 [%0], {%1,%2,%3,%4};" ::"r"(a), "r"(r[0]), "r"(r[1]), "r"(r[2]), "r"(r[3]) : "memory");
}
__device__ __forceinline__ void stg128(void* p, const uint32_t* r) {
  asm volatile("st.global.v4.u32 [%0], {%1,%2,%3,%4};" ::"l"(p), "r"(r[0]), "r"(r[1]), "r"(r[2]), "r"(r[3]) : "memory");
}
__device__ __forceinline__ uint32_t pack_bf16(float lo, float hi) {
  uint32_t r;
  asm("cvt.rn.bf16x2.f32 %0, %1, %2;" : "=r"(r) : "f"(hi), "f"(lo));
  return r;
}
__device__ __forceinline__ float bf_lo(uint32_t v) { return __uint_as_float(v << 16); }
__device__ __forceinline__ float bf_hi(uint32_t v) { return __uint_as_float(v & 0xffff0000u); }
__device__ __forceinline__ float round_bf16(float v) { return __bfloat162float(__float2bfloat16(v)); }
__device__ __forceinline__ uint32_t mul_bf16x2(uint32_t a, uint32_t b) {
  uint32_t r;
  asm("mul.rn.bf16x2 %0, %1, %2;" : "=r"(r) : "r"(a), "r"(b));
  return r;
}
__device__ __forceinline__ uint32_t sub_bf16x2(uint32_t a, uint32_t b) {
  uint32_t r;
  asm("sub.rn.bf16x2 %0, %1, %2;" : "=r"(r) : "r"(a), "r"(b));
  return r;
}
__device__ __forceinline__ float ex2f(float x) { float r; asm("ex2.approx.ftz.f32 %0, %1;" : "=f"(r) : "f"(x)); return r; }
__device__ __forceinline__ float rcpf(float x) { float r; asm("rcp.approx.ftz.f32 %0, %1;" : "=f"(r) : "f"(x)); return r; }

#define ACC32(c, d)                                                                                        \
  c(d[0]), c(d[1]), c(d[2]), c(d[3]), c(d[4]), c(d[5]), c(d[6]), c(d[7]), c(d[8]), c(d[9]), c(d[10]),      \
      c(d[11]), c(d[12]), c(d[13]), c(d[14]), c(d[15]), c(d[16]), c(d[17]), c(d[18]), c(d[19]), c(d[20]),  \
      c(d[21]), c(d[22]), c(d[23]), c(d[24]), c(d[25]), c(d[26]), c(d[27]), c(d[28]), c(d[29]), c(d[30]), c(d[31])
#define REGS32                                                                                             \
  "{%0,%1,%2,%3,%4,%5,%6,%7,%8,%9,%10,%11,%12,%13,%14,%15,%16,%17,%18,%19,%20,%21,%22,%23,%24,%25,%26,%27,%28,%29,%30,%31}"

template <bool FIRST, int OFF>
__device__ __forceinline__ void wgmma64(float (&d)[32], const uint32_t* a, uint32_t dlo) {
  if constexpr (FIRST) {
    asm volatile("{\n.reg .pred p;\n.reg .b32 t;\n.reg .b64 db;\nsetp.ne.b32 p, 0, 0;\nadd.u32 t, %36, %37;\nmov.b64 db, {t, 0x40000040};\n"
                 "wgmma.mma_async.sync.aligned.m64n64k16.f32.bf16.bf16 " REGS32 ", {%32,%33,%34,%35}, db, p, 1, 1, 1;\n}\n"
                 : ACC32("=f", d) : "r"(a[0]), "r"(a[1]), "r"(a[2]), "r"(a[3]), "r"(dlo), "n"(OFF));
  } else {
    asm volatile("{\n.reg .pred p;\n.reg .b32 t;\n.reg .b64 db;\nsetp.eq.b32 p, 0, 0;\nadd.u32 t, %36, %37;\nmov.b64 db, {t, 0x40000040};\n"
                 "wgmma.mma_async.sync.aligned.m64n64k16.f32.bf16.bf16 " REGS32 ", {%32,%33,%34,%35}, db, p, 1, 1, 1;\n}\n"
                 : ACC32("+f", d) : "r"(a[0]), "r"(a[1]), "r"(a[2]), "r"(a[3]), "r"(dlo), "n"(OFF));
  }
}
__device__ __forceinline__ void wg_fence() { asm volatile("wgmma.fence.sync.aligned;" ::: "memory"); }
__device__ __forceinline__ void wg_commit() { asm volatile("wgmma.commit_group.sync.aligned;" ::: "memory"); }
template <int N>
__device__ __forceinline__ void wg_wait() { asm volatile("wgmma.wait_group.sync.aligned %0;" ::"n"(N) : "memory"); }
__device__ __forceinline__ void pin(float& v) { asm volatile("" : "+f"(v)::"memory"); }
__device__ __forceinline__ void pin(uint32_t& v) { asm volatile("" : "+r"(v)::"memory"); }

#define NOTRIG 5
#define CREG "240"
#define NOPDL 0
#define MAPB 0
#define TANH 1
#define LDSPLIT 0
#define MOV8 0
#define PF 0
#define TMP 1
#define EARLYX 0
#define VARP 0
constexpr int kSlotBytes = 12288, kPasses = 27, kBoxRows = 48;
constexpr uint32_t oR = 0, kRWg = 9 * 8192, oW = 2 * kRWg, oBar = oW + 6 * kSlotBytes;
constexpr uint32_t bFull = oBar, bEmpty = bFull + 48, bX = bEmpty + 48, bP0 = bX + 96, bTag = bP0 + 8, oK = bTag + 8, oTag = oK + 256, oEnd = oTag + 8;
constexpr int kFfnSmem = oEnd;
static_assert(bX == oBar + 96 && bP0 == oBar + 192 && bTag == oBar + 200, "barrier layout");

__device__ __forceinline__ uint4* part_ptr(int mt, int blk, int slot) { return g_part + ((mt * 9 + blk) * 9 + slot) * 1024; }

#define XWIN 12
#define XD 0
#define WD 2
#define WK 1
#define SLD 3
#define SUN 2
#define SLAST 3
struct Ctx {
  uint32_t sb;
  uint32_t relbar;
  bool rel, always;
  uint32_t priv;
  float c0, c1;
  uint32_t ready;
  uint32_t tag;
  const uint4* src;
  uint4* dst;
};

__device__ __forceinline__ uint32_t mbar_probe(uint32_t b, uint32_t parity) {
  uint32_t ok;
  asm volatile("{\n.reg .pred p;\nmbarrier.test_wait.parity.shared::cta.b64 p, [%1], %2;\nselp.u32 %0, 1, 0, p;\n}\n"
               : "=r"(ok) : "r"(b), "r"(parity) : "memory");
  return ok;
}
__device__ __forceinline__ uint32_t frag_index() { return (threadIdx.x >> 5) * 128 + (threadIdx.x & 31); }
__device__ __forceinline__ void ldg_relaxed(uint32_t* v, const uint4* p) {
  asm volatile("{\n.reg .b128 t;\n.reg .b64 lo, hi;\nld.relaxed.gpu.global.b128 t, [%4];\nmov.b128 {lo, hi}, t;\nmov.b64 {%0, %1}, lo;\nmov.b64 {%2, %3}, hi;\n}\n"
               : "=r"(v[0]), "=r"(v[1]), "=r"(v[2]), "=r"(v[3]) : "l"(p) : "memory");
}
__device__ __forceinline__ void stg_relaxed(uint4* p, const uint32_t* v) {
  asm volatile("{\n.reg .b128 t;\n.reg .b64 lo, hi;\nmov.b64 lo, {%1, %2};\nmov.b64 hi, {%3, %4};\nmov.b128 t, {lo, hi};\nst.relaxed.gpu.global.b128 [%0], t;\n}\n"
               ::"l"(p), "r"(v[0]), "r"(v[1]), "r"(v[2]), "r"(v[3]) : "memory");
}
__device__ __forceinline__ void ensure_landed(uint32_t* v, const uint4* p, uint32_t tag) {
#pragma unroll 1
  for (int it = 0; it < 2000000 && ((v[0] ^ tag) & 1); it++) ldg_relaxed(v, p);
}
__device__ __forceinline__ void load_tile(uint32_t (&v)[16], const uint4* p) {
#pragma unroll
  for (int q = 0; q < 4; q++) ldg_relaxed(&v[4 * q], p + q * 32);
}
__device__ __forceinline__ void ensure_tile(uint32_t (&v)[16], const uint4* p, uint32_t tag) {
#pragma unroll 1
  for (int it = 0; it < 2000000; it++) {
    const uint32_t m = (v[0] ^ tag) | (v[4] ^ tag) | (v[8] ^ tag) | (v[12] ^ tag);
    if (!__any_sync(0xffffffffu, m & 1)) break;
    load_tile(v, p);
  }
}
__device__ __forceinline__ uint32_t add_bf16x2(uint32_t a, uint32_t b) {
  uint32_t r;
  asm("add.rn.bf16x2 %0, %1, %2;" : "=r"(r) : "r"(a), "r"(b));
  return r;
}
__device__ __forceinline__ uint32_t fma_bf16x2(uint32_t a, uint32_t b, uint32_t c) {
  uint32_t r;
  asm("fma.rn.bf16x2 %0, %1, %2, %3;" : "=r"(r) : "r"(a), "r"(b), "r"(c));
  return r;
}
template <int G>
__device__ __forceinline__ void centre_group(uint32_t (&A)[144], uint32_t m0, uint32_t m1) {
#pragma unroll
  for (int i = 24 * G; i < 24 * G + 24; i++) { A[i] = sub_bf16x2(A[i], (i & 1) ? m1 : m0); pin(A[i]); }
}
template <bool SUB>
__device__ __forceinline__ void square_group(const uint32_t* a, uint32_t p0, uint32_t p1, float& q0, float& q1) {
#pragma unroll
  for (int k = 0; k < 4; k++) {
    uint32_t t = 0;
#pragma unroll
    for (int j = 0; j < 6; j++) {
      const uint32_t v = a[(k >> 1) * 12 + (k & 1) + 2 * j], d = SUB ? sub_bf16x2(v, (k & 1) ? p1 : p0) : v;
      t = j ? fma_bf16x2(d, d, t) : mul_bf16x2(d, d);
    }
    if (k & 1) q1 += bf_lo(t) + bf_hi(t); else q0 += bf_lo(t) + bf_hi(t);
  }
  pin(q0); pin(q1);
}
template <typename T>
__device__ __forceinline__ void pinp(T*& v) { asm volatile("" : "+l"(v)::"memory"); }

constexpr int kAhead = 3;
__device__ __forceinline__ void prefetch_pass(const char* w1, const char* w3, const char* w2, int p, int f, int row) {
  const char* a = p < 18 ? ((p & 1) ? w3 : w1) + (size_t)row * (kF * 2) + f * 1152 + (p >> 1) * 128
                         : w2 + (size_t)(f * 576 + row) * (kD * 2) + (p == 18 ? 8 : ((f + p - 18) & 7)) * 128;
  asm volatile("prefetch.global.L2 [%0];" ::"l"(a));
}

enum Kind { K_FIRST, K_GATE, K_UP, K_XCHG };

template <int KIND, bool ODD, int S>
__device__ __forceinline__ void epi_slice(Ctx& c, uint32_t (&A)[144], float (&p)[32], uint32_t (&Sv)[16], int n, int mt, int f) {
  if constexpr (KIND == K_FIRST) {
    if constexpr (S < 5) centre_group<S + 1>(A, Sv[0], Sv[1]);
    if constexpr (S < 5 && (!VARP || S == 4)) square_group<false>(&A[24 * S + 24], 0, 0, c.c0, c.c1);
    if (S == 1) {
#pragma unroll
      for (int kk = 0; kk < 4; kk++) ldsm4t((uint32_t*)&p[kk * 4], Sv[4] + kk * 2048);
    }
    if (S == 3) {
#pragma unroll
      for (int q = 0; q < 4; q++) sts128(c.priv + 8 * 8192 + q * 512, (uint32_t*)&p[4 * q]);
    }
    if (S == 5) {
#pragma unroll
      for (int m = 1; m <= 2; m++) { c.c0 += __shfl_xor_sync(0xffffffffu, c.c0, m); c.c1 += __shfl_xor_sync(0xffffffffu, c.c1, m); }
      const float e0 = __uint_as_float(Sv[2]), e1 = __uint_as_float(Sv[3]);
      const float v0 = fmaxf(c.c0 * (1.f / kD) - e0 * e0, 0.f), v1 = fmaxf(c.c1 * (1.f / kD) - e1 * e1, 0.f);
      float d0, d1;
      asm("sqrt.approx.f32 %0, %1;" : "=f"(d0) : "f"(round_bf16(round_bf16(v0) + 1e-5f)));
      asm("sqrt.approx.f32 %0, %1;" : "=f"(d1) : "f"(round_bf16(round_bf16(v1) + 1e-5f)));
      c.c0 = (TANH ? 0.5f : -1.4426950408889634f) * rcpf(round_bf16(d0)); c.c1 = (TANH ? 0.5f : -1.4426950408889634f) * rcpf(round_bf16(d1));
      pin(c.c0); pin(c.c1);
    }
  } else if constexpr (KIND == K_GATE) {
    constexpr int lo = S < 4 ? S * 3 : 4 + S * 2, hi = S < 4 ? S * 3 + 3 : 6 + S * 2;
    if (S == 0 || c.always) {
#pragma unroll
      for (int i = lo; i < hi; i++) {
        pin(p[2 * i]); pin(p[2 * i + 1]);
        const float k = (i & 1) ? c.c1 : c.c0;
        const float t0 = p[2 * i] * k, t1 = p[2 * i + 1] * k;
        if (TANH) {
          float h0, h1;
          asm("tanh.approx.f32 %0, %1;" : "=f"(h0) : "f"(t0));
          asm("tanh.approx.f32 %0, %1;" : "=f"(h1) : "f"(t1));
          Sv[i] = pack_bf16(fmaf(t0, h0, t0), fmaf(t1, h1, t1));
        } else {
          Sv[i] = pack_bf16(t0 * rcpf(1.f + ex2f(t0)), t1 * rcpf(1.f + ex2f(t1)));
        }
        pin(Sv[i]);
      }
    }
    if (S >= 1 && n == 8) {
#pragma unroll
      for (int q = 6 * (S - 1); q < 6 * S; q++) lds128(&A[4 * q], c.priv + (q >> 2) * 8192 + (q & 3) * 512);
    }
  } else if constexpr (KIND == K_UP) {
    if (S < 4) {
#pragma unroll
      for (int i = 4 * S; i < 4 * S + 4; i++) {
        pin(p[2 * i]); pin(p[2 * i + 1]);
        Sv[i] = mul_bf16x2(Sv[i], pack_bf16(p[2 * i], p[2 * i + 1]));
      }
      if (!MOV8 || n < 8) sts128(c.priv + (n & 7) * 8192 + S * 512, &Sv[4 * S]);
      else {
#pragma unroll
        for (int i = 4 * S; i < 4 * S + 4; i++) { A[128 + i] = Sv[i]; pin(A[128 + i]); }
      }
    }
    if (S == 3 && n == 8) {
#pragma unroll
      for (int q = 30; q < (MOV8 ? 32 : 36); q++) lds128(&A[4 * q], c.priv + ((q >> 2) & 7) * 8192 + (q & 3) * 512);
    }
  } else {
    if (S == 0) {
      uint32_t v[16];
#pragma unroll
      for (int i = 0; i < 16; i++) {
        pin(p[2 * i]); pin(p[2 * i + 1]);
        v[i] = pack_bf16(p[2 * i], p[2 * i + 1]);
        if ((i & 3) == 0) v[i] = (v[i] & ~1u) | c.tag;
      }
#pragma unroll
      for (int q = 0; q < 4; q++) stg_relaxed(c.dst + q * 32, &v[4 * q]);
    }
    if (S == 2) {
      c.dst = part_ptr(mt, (f + n) & 7, f) + frag_index();
      pinp(c.dst);
    }
    if (S == SUN) {
      if (n >= 4) ensure_tile(Sv, c.src, c.tag);
#pragma unroll
      for (int i = 0; i < 16; i++) { p[2 * i] = bf_lo(Sv[i]); p[2 * i + 1] = bf_hi(Sv[i]); pin(p[2 * i]); pin(p[2 * i + 1]); }
      c.src = (n < 7 ? part_ptr(mt, (f + n + 2) & 7, f ^ 4) : part_ptr(mt, f, (f + 10 - n) & 7)) + frag_index();
      pinp(c.src);
    }
    if (S == SLD && n >= 3) load_tile(Sv, c.src);
  }
}

template <int KIND, bool ODD, int S>
__device__ __forceinline__ void stage(Ctx& c, uint32_t (&A)[144], float (&d)[32], float (&p)[32], uint32_t (&Sv)[16], int n, int mt, int f) {
  if (!c.ready) mbar_wait(c.sb + bFull + S * 8, ODD);
  const uint32_t dlo = ((c.sb + oW) & 0x3FFFF) >> 4;
  constexpr int o = S * (kSlotBytes >> 4);
  wg_fence();
  wgmma64<S == 0 && KIND != K_XCHG, o>(d, &A[S * 24], dlo);
  wgmma64<false, o + 128>(d, &A[S * 24 + 4], dlo);
  wgmma64<false, o + 256>(d, &A[S * 24 + 8], dlo);
  wgmma64<false, o + 384>(d, &A[S * 24 + 12], dlo);
  wgmma64<false, o + 512>(d, &A[S * 24 + 16], dlo);
  wgmma64<false, o + 640>(d, &A[S * 24 + 20], dlo);
  wg_commit();
  if (KIND != K_FIRST || S > 0) {
    wg_wait<1>();
    if (c.rel) mbar_arrive_cluster(c.relbar + ((S + 5) % 6) * 8);
  }
  c.ready = mbar_probe(c.sb + bFull + ((S + 1) % 6) * 8, S == 5 ? !ODD : ODD);
  epi_slice<KIND, ODD, S>(c, A, p, Sv, n, mt, f);
}

template <int KIND, bool ODD>
__device__ __forceinline__ void pass(Ctx& c, uint32_t (&A)[144], float (&d)[32], float (&p)[32], uint32_t (&Sv)[16], int n, int mt, int f) {
  stage<KIND, ODD, 0>(c, A, d, p, Sv, n, mt, f);
  stage<KIND, ODD, 1>(c, A, d, p, Sv, n, mt, f);
  stage<KIND, ODD, 2>(c, A, d, p, Sv, n, mt, f);
  stage<KIND, ODD, 3>(c, A, d, p, Sv, n, mt, f);
  stage<KIND, ODD, 4>(c, A, d, p, Sv, n, mt, f);
  stage<KIND, ODD, 5>(c, A, d, p, Sv, n, mt, f);
}

__global__ void __cluster_dims__(2, 1, 1) __launch_bounds__(384, 1)
ffn_kernel(const __grid_constant__ CUtensorMap tmW1, const __grid_constant__ CUtensorMap tmW3,
           const __grid_constant__ CUtensorMap tmW2, __nv_bfloat16* __restrict__ out, int one) {
  extern __shared__ __align__(1024) unsigned char smem_raw[];
  const uint32_t sb = smem_u32(smem_raw);
  const int rank = blockIdx.x & 1, pr = blockIdx.x >> 1;
  const int q7 = ((pr - 36) * 37) >> 8;
  const int grp = pr < 4 ? 7 : (pr < 36 ? (pr - 4) & 7 : pr - 36 - 7 * q7);
  const int mt = 2 * grp + rank, f = pr < 4 ? 4 + pr : (pr < 36 ? (pr - 4) >> 3 : 4 + q7);
  const int warp = __shfl_sync(0xffffffffu, threadIdx.x >> 5, 0), lane = threadIdx.x & 31;

  if (warp == 10) {
    if (elect_one()) {
#pragma unroll
      for (int i = 0; i < 12; i++) mbar_init(sb + bX + i * 8, 1);
      mbar_init(sb + bTag, 1);
      asm volatile("fence.mbarrier_init.release.cluster;" ::: "memory");
    }
  } else if (warp == 8) {
    if (elect_one()) {
#pragma unroll
      for (int i = 0; i < 6; i++) { mbar_init(sb + bFull + i * 8, 1); mbar_init(sb + bEmpty + i * 8, 4); }
      mbar_init(sb + bP0, 32);
      asm volatile("fence.mbarrier_init.release.cluster;" ::: "memory");
    }
  } else if (TMP && warp == 9) {
    if (elect_one()) asm volatile("prefetch.tensormap [%0];" ::"l"(&tmW1) : "memory");
  }
  __syncwarp();
  asm volatile("barrier.cluster.arrive.relaxed.aligned;" ::: "memory");
  if (!EARLYX || warp != 10) asm volatile("barrier.cluster.wait.aligned;" ::: "memory");

  if (warp >= 8) {
    asm volatile("setmaxnreg.dec.sync.aligned.u32 24;");
    if (warp <= 9) {
      if (elect_one()) {
        const int w = warp - 8;
#pragma unroll 1
        for (int p = 0; p < kPasses; p++) {
          const CUtensorMap* tm = p >= 18 ? &tmW2 : ((p & 1) ? &tmW3 : &tmW1);
          const int x = p >= 18 ? (p == 18 ? 8 : ((f + p - 18) & 7)) * 64 : f * 576 + (p >> 1) * 64;
          const int y = (p >= 18 ? f * 576 : 0) + rank * 48 + w * 96;
#pragma unroll
          for (int k = 0; k < 3; k++) {
            const uint32_t bo = (2 * k + w) * 8;
            if (p) mbar_wait(sb + bEmpty + bo, (p - 1) & 1);
            else if (WD >= 0 && k == WK) mbar_wait(sb + bX + WD * 8, 0);
            mbar_expect(sb + bFull + bo, kSlotBytes);
            tma2d_mc(sb + oW + (2 * k + w) * kSlotBytes + rank * 6144, tm, sb + bFull + bo, x, y + k * 192);
          }
        }
        for (int k = 0; k < 3; k++)
          if (2 * k + w < 5) mbar_wait(sb + bEmpty + (2 * k + w) * 8, 0);
      }
    } else {
      const int w = warp - 10;
      if (w == 0) {
        if (elect_one()) {
#pragma unroll
          for (int i = 0; i < XWIN; i++) mbar_expect(sb + bX + i * 8, 12288);
          asm volatile("griddepcontrol.wait;" ::: "memory");
#pragma unroll
          for (int i = 0; i < 12; i++) {
            if (i >= XWIN) { mbar_expect(sb + bX + i * 8, 12288); mbar_wait(sb + bX + (i - XWIN + XD < 0 ? 0 : i - XWIN + XD) * 8, 0); }
            bulk_g2s(sb + oR + i * 12288, (const char*)g_hT + (size_t)mt * 147456 + i * 12288, 12288, sb + bX + i * 8);
          }
          asm volatile("st.shared.u32 [%0], %1;" ::"r"(sb + oTag), "r"(__ldcg(&g_epoch) & 1) : "memory");
          mbar_arrive(sb + bTag);
          if (blockIdx.x < 64) g_lncnt[blockIdx.x * 64] = 0;
        }
        __syncwarp();
        if (EARLYX) asm volatile("barrier.cluster.wait.aligned;" ::: "memory");
      } else {
#pragma unroll 1
        for (int p = kAhead; p < 18; p++) {
          mbar_wait(sb + bFull + 16, (p - kAhead) & 1);
          if (mt < 576 / kBoxRows && elect_one()) {
            tma_prefetch((p & 1) ? &tmW3 : &tmW1, f * 576 + (p >> 1) * 64, mt * kBoxRows);
            if (p >= 9) tma_prefetch(&tmW2, (p == 9 ? 8 : ((f + p - 9) & 7)) * 64, f * 576 + mt * kBoxRows);
          }
        }
      }
      mbar_wait(sb + bP0, 0);
      uint32_t tag;
      asm volatile("ld.shared.u32 %0, [%1];" : "=r"(tag) : "r"(sb + oTag) : "memory");
#pragma unroll 1
      for (int q = 2 * w; q < 2 * w + 2; q++) {
        const uint4* src = part_ptr(mt, 8, 0) + f * 128 + q * 32 + lane;
        float a[8] = {0.f, 0.f, 0.f, 0.f, 0.f, 0.f, 0.f, 0.f};
#pragma unroll 1
        for (int s = 0; s < 8; s += 2) {
          uint32_t v[8];
          ldg_relaxed(v, src);
          ldg_relaxed(v + 4, src + 1024);
          ensure_landed(v, src, tag);
          ensure_landed(v + 4, src + 1024, tag);
#pragma unroll
          for (int i = 0; i < 4; i++) { a[2 * i] += bf_lo(v[i]) + bf_lo(v[4 + i]); a[2 * i + 1] += bf_hi(v[i]) + bf_hi(v[4 + i]); }
          src += 2048;
        }
        {
          uint32_t v[4];
          float k0, k1;
          ldg_relaxed(v, src);
          asm volatile("ld.shared.v2.f32 {%0, %1}, [%2];" : "=f"(k0), "=f"(k1) : "r"(sb + oK + lane * 8) : "memory");
#pragma unroll
          for (int i = 0; i < 4; i++) {
            a[2 * i] = fmaf(a[2 * i], (i & 1) ? k1 : k0, bf_lo(v[i]));
            a[2 * i + 1] = fmaf(a[2 * i + 1], (i & 1) ? k1 : k0, bf_hi(v[i]));
          }
        }
        uint32_t* o = (uint32_t*)(out + (size_t)(mt * 128 + f * 16 + (lane >> 2)) * kD + 512 + q * 16 + (lane & 3) * 2);
        o[0] = pack_bf16(a[0], a[1]);
        o[4] = pack_bf16(a[4], a[5]);
        o[8 * kD / 2] = pack_bf16(a[2], a[3]);
        o[8 * kD / 2 + 4] = pack_bf16(a[6], a[7]);
      }
    }
  } else {
    asm volatile("setmaxnreg.inc.sync.aligned.u32 " CREG ";");
    const int wg = warp >> 2, tid = threadIdx.x & 127;
    Ctx c;
    c.sb = sb;
    c.rel = (tid & 0x5f) == 0;
    c.relbar = mapa(sb + bEmpty, warp & 1);
    c.priv = sb + oR + wg * kRWg + (warp & 3) * 2048 + lane * 16;
    pin(c.priv);
    c.ready = 0;
    c.always = one != 0;
    uint32_t A[144];
    float acc0[32], acc1[32];
    uint32_t Sv[16];
    {
      const uint32_t row = (lane >> 4) * 8 + (lane & 7);
      const uint32_t chunk = (2 * (warp & 3) + ((lane >> 3) & 1)) ^ (lane & 7);
      const uint32_t base = sb + oR + wg * kRWg + row * 128 + chunk * 16;
      float s0 = 0.f, s1 = 0.f, q0 = 0.f, q1 = 0.f, t0, t1;
      uint32_t p0, p1;
#pragma unroll
      for (int g = 0; g < 6; g++) {
        mbar_wait(sb + bX + (wg * 6 + g) * 8, 0);
#pragma unroll
        for (int kk = 0; kk < 6; kk++) ldsm4t(&A[g * 24 + kk * 4], base + g * 12288 + kk * 2048);
#pragma unroll
        for (int k = 0; k < 6; k++) {
          const int i = 24 * g + (k >> 1) * 8 + (k & 1);
          const uint32_t t = add_bf16x2(add_bf16x2(A[i], A[i + 2]), add_bf16x2(A[i + 4], A[i + 6]));
          if (k & 1) s1 += bf_lo(t) + bf_hi(t); else s0 += bf_lo(t) + bf_hi(t);
        }
        pin(s0); pin(s1);
        if (VARP) {
          if (g == 0) { p0 = pack_bf16(s0 * (1.f / 24), s0 * (1.f / 24)); p1 = pack_bf16(s1 * (1.f / 24), s1 * (1.f / 24)); }
          if (g < 5) square_group<true>(&A[24 * g], p0, p1, q0, q1);
          if (g == 4) { t0 = s0; t1 = s1; }
        }
      }
#pragma unroll
      for (int m = 1; m <= 2; m++) { s0 += __shfl_xor_sync(0xffffffffu, s0, m); s1 += __shfl_xor_sync(0xffffffffu, s1, m); }
      if (warp == f) {
        uint4* dst = part_ptr(mt, 8, 8) + frag_index();
#pragma unroll
        for (int j = 0; j < 4; j++) stg128(dst + j * 32, &A[128 + j * 4]);
      }
      const float m0 = s0 * (1.f / kD), m1 = s1 * (1.f / kD);
      Sv[0] = pack_bf16(m0, m0); Sv[1] = pack_bf16(m1, m1);
      Sv[2] = __float_as_uint(m0 - bf_lo(Sv[0])); Sv[3] = __float_as_uint(m1 - bf_lo(Sv[1]));
      Sv[4] = base + f * 8192;
      centre_group<0>(A, Sv[0], Sv[1]);
      if (VARP) {
        const float d0 = bf_lo(Sv[0]) - bf_lo(p0), d1 = bf_lo(Sv[1]) - bf_lo(p1);
        c.c0 = fmaf(d0, fmaf(120.f, d0, -2.f * fmaf(-120.f, bf_lo(p0), t0)), q0);
        c.c1 = fmaf(d1, fmaf(120.f, d1, -2.f * fmaf(-120.f, bf_lo(p1), t1)), q1);
      } else {
        c.c0 = c.c1 = 0.f;
        square_group<false>(&A[0], 0, 0, c.c0, c.c1);
      }
    }
    pass<K_FIRST, false>(c, A, acc0, acc1, Sv, 0, mt, f);
#pragma unroll 1
    for (int n = 0; n < 9; n++) {
      pass<K_GATE, true>(c, A, acc1, acc0, Sv, n, mt, f);
      pass<K_UP, false>(c, A, acc0, acc1, Sv, n, mt, f);
    }
    c.c0 *= TANH ? 2.f : 0.4804530139182014f; c.c1 *= TANH ? 2.f : 0.4804530139182014f;
    if (warp == f) asm volatile("st.shared.v2.f32 [%0], {%1, %2};" ::"r"(sb + oK + lane * 8), "f"(c.c0), "f"(c.c1) : "memory");
#pragma unroll
    for (int i = 0; i < 32; i++) acc1[i] = 0.f;
    c.src = nullptr;
#pragma unroll
    for (int i = 0; i < 16; i++) Sv[i] = 0;
    c.dst = part_ptr(mt, 8, f) + frag_index();
    mbar_wait(sb + bTag, 0);
    asm volatile("ld.shared.u32 %0, [%1];" : "=r"(c.tag) : "r"(sb + oTag) : "memory");
#pragma unroll 1
    for (int n = 1; n < 9; n += 2) {
      pass<K_XCHG, true>(c, A, acc1, acc0, Sv, n, mt, f);
      if (n == 1 && warp == f) mbar_arrive(sb + bP0);
      pass<K_XCHG, false>(c, A, acc0, acc1, Sv, n + 1, mt, f);
    }
    {
      uint32_t hv[16], last[16];
      const uint4* lsrc = part_ptr(mt, f, (f + 1) & 7) + frag_index();
      load_tile(last, lsrc);
#pragma unroll
      for (int q = 0; q < 4; q++) lds128(&hv[4 * q], c.priv + 8 * 8192 + q * 512);
      ensure_tile(Sv, c.src, c.tag);
#pragma unroll
      for (int i = 0; i < 16; i++) {
        const float k = (i & 1) ? c.c1 : c.c0;
        acc1[2 * i] = fmaf(acc1[2 * i] + bf_lo(Sv[i]), k, bf_lo(hv[i]));
        acc1[2 * i + 1] = fmaf(acc1[2 * i + 1] + bf_hi(Sv[i]), k, bf_hi(hv[i]));
        pin(acc1[2 * i]); pin(acc1[2 * i + 1]);
      }
      wg_wait<0>();
#pragma unroll
      for (int i = 0; i < 32; i++) { pin(acc0[i]); acc1[i] = fmaf(acc0[i], (i & 2) ? c.c1 : c.c0, acc1[i]); pin(acc1[i]); }
      ensure_tile(last, lsrc, c.tag);
      __syncwarp();
      const uint32_t stg = sb + oR + wg * kRWg + 2 * 8192 + (warp & 3) * 2048;
      const uint32_t ra = stg + (((lane >> 3) & 1) * 8 + (lane & 7)) * 128;
#pragma unroll
      for (int j = 0; j < 4; j++) {
        uint32_t v[4];
#pragma unroll
        for (int i = 0; i < 4; i++) {
          const int e = 8 * j + 2 * i;
          const float k = (i & 1) ? c.c1 : c.c0;
          v[i] = pack_bf16(fmaf(bf_lo(last[4 * j + i]), k, acc1[e]), fmaf(bf_hi(last[4 * j + i]), k, acc1[e + 1]));
        }
        stsm4(ra + (((2 * j + (lane >> 4)) ^ (lane & 7)) << 4), v[0], v[1], v[2], v[3]);
      }
      __syncwarp();
#pragma unroll
      for (int i = 0; i < 4; i++) {
        const uint32_t rr = 4 * i + (lane >> 3);
        uint32_t v[4];
        lds128(v, stg + rr * 128 + (((lane & 7) ^ (rr & 7)) << 4));
        stg128(out + (size_t)(mt * 128 + warp * 16 + rr) * kD + f * 64 + (lane & 7) * 8, v);
      }
    }
  }
}

#define J1 0
#define L1 -1
#define SMR 1
#define EG 0
constexpr int kSsmThreads = 768;
constexpr uint32_t kUPad = 256, kUCh = kUPad + 4096;
constexpr uint32_t kKeWords = 16 + 544, kCWords = 96;
constexpr uint32_t kTabCh = 3072;
constexpr uint32_t kFacRow = 272, kFacHalf = 54 * kFacRow;
constexpr uint32_t kQ4Pad = 64, kQ4Words = kQ4Pad + 1568, kQ8Pad = 128, kQ8Words = kQ8Pad + 1024;
constexpr uint32_t kQCh = (kQ4Words + kQ8Words) * 4;
constexpr uint32_t kLnRow = 1168, kLnX = 16 * kLnRow + 64;
constexpr uint32_t aU = 0, aX = aU + 5 * kUCh, aTab = aX + 5 * 4096, aFac = aTab + 5 * kTabCh,
                   aBar = aFac + 10 * kFacHalf + 640, aEnd = aBar + 32;
constexpr uint32_t aQ = aFac, aOut = aQ + 5 * kQCh;
constexpr int kSsmSmem = aEnd;
static_assert(aOut + 12 * 2048 <= aBar, "smem");
static_assert(kLnX <= 5 * kUCh && kLnX <= 5 * 4096, "smem");
static_assert((kKeWords + 2 * kCWords) * 4 <= kTabCh, "smem");
static_assert(aTab % 128 == 0 && aFac % 128 == 0 && kQCh % 128 == 0 && aBar % 8 == 0 && kSsmSmem <= 232448, "smem");

struct Cx { float r, i; };
__device__ __forceinline__ Cx cmul(Cx a, Cx b) { return {fmaf(a.r, b.r, -a.i * b.i), fmaf(a.r, b.i, a.i * b.r)}; }
__device__ __forceinline__ Cx csqr(Cx a) { return {fmaf(a.r, a.r, -a.i * a.i), (a.r + a.r) * a.i}; }
__device__ __forceinline__ Cx cexp_scaled(float lr, float turns, float e) {
  const float t = turns * e, fr = (t - rintf(t)) * 6.283185307179586f, m = ex2f(lr * e);
  return {m * __cosf(fr), m * __sinf(fr)};
}
__device__ __forceinline__ uint32_t ldg32(const void* p) { uint32_t v; asm volatile("ld.volatile.global.u32 %0, [%1];" : "=r"(v) : "l"(p) : "memory"); return v; }
__device__ __forceinline__ uint32_t ldg16(const void* p) { uint32_t v; asm volatile("ld.volatile.global.u16 %0, [%1];" : "=r"(v) : "l"(p) : "memory"); return v; }
__device__ __forceinline__ void sts16(uint32_t a, uint32_t v) { asm volatile("st.shared.u16 [%0], %1;" ::"r"(a), "r"(v) : "memory"); }
__device__ __forceinline__ void sts32(uint32_t a, uint32_t v) { asm volatile("st.shared.u32 [%0], %1;" ::"r"(a), "r"(v) : "memory"); }
__device__ __forceinline__ void sts64(uint32_t a, uint32_t v0, uint32_t v1) { asm volatile("st.shared.v2.u32 [%0], {%1, %2};" ::"r"(a), "r"(v0), "r"(v1) : "memory"); }
__device__ __forceinline__ uint32_t lds32(uint32_t a) { uint32_t v; asm volatile("ld.shared.u32 %0, [%1];" : "=r"(v) : "r"(a) : "memory"); return v; }
__device__ __forceinline__ void ldsm4(uint32_t* r, uint32_t a) {
  asm volatile("ldmatrix.sync.aligned.m8n8.x4.shared.b16 {%0,%1,%2,%3}, [%4];"
               : "=r"(r[0]), "=r"(r[1]), "=r"(r[2]), "=r"(r[3]) : "r"(a) : "memory");
}
__device__ __forceinline__ void stsm4t(uint32_t a, uint32_t r0, uint32_t r1, uint32_t r2, uint32_t r3) {
  asm volatile("stmatrix.sync.aligned.m8n8.x4.trans.shared.b16 [%0], {%1,%2,%3,%4};" ::"r"(a), "r"(r0), "r"(r1), "r"(r2), "r"(r3) : "memory");
}
__device__ __forceinline__ void mma16816(float* d, uint32_t a0, uint32_t a1, uint32_t a2, uint32_t a3, uint32_t b0, uint32_t b1) {
  asm volatile("mma.sync.aligned.m16n8k16.row.col.f32.bf16.bf16.f32 {%0,%1,%2,%3}, {%4,%5,%6,%7}, {%8,%9}, {%0,%1,%2,%3};"
               : "+f"(d[0]), "+f"(d[1]), "+f"(d[2]), "+f"(d[3]) : "r"(a0), "r"(a1), "r"(a2), "r"(a3), "r"(b0), "r"(b1));
}
__device__ __forceinline__ void bar_sync(int id, int n) { asm volatile("bar.sync %0, %1;" ::"r"(id), "r"(n) : "memory"); }
__device__ __forceinline__ void bar_arrive(int id, int n) { asm volatile("bar.arrive %0, %1;" ::"r"(id), "r"(n) : "memory"); }
__device__ __forceinline__ int slot_channel(int b, int s) { return s < 4 ? 4 * b + s : 512 + (b >> 1); }

template <bool HI>
__device__ __forceinline__ void conv_unit(uint32_t sb, int slot, int ch, int warp, int lane, uint32_t zero) {
  constexpr int O0 = HI ? 8 : 0;
  const int g = lane >> 2, t = lane & 3;
  const uint32_t tab = sb + aTab + slot * kTabCh;
  float acc[8][4];
#pragma unroll
  for (int o = 0; o < 8; o++) acc[o][0] = acc[o][1] = acc[o][2] = acc[o][3] = 0.f;

  uint32_t ke = tab + (16 + g - 2 * t) * 4;
  uint32_t lin = sb + aU + slot * kUCh + kUPad + (lane & 7) * 32 + (lane >> 4) * 256 + ((lane >> 3) & 1) * 16;
  uint32_t am[4];
#pragma unroll
  for (int q = 0; q < 4; q++) am[q] = lds32(ke + (128 * q - 8) * 4);
#pragma unroll 1
  for (int rho = 0; rho < 8; rho++) {
    constexpr int X0 = HI ? 4 : 0, NX = HI ? 12 : 8;
    const uint32_t ga = lin ^ ((lin >> 3) & 16);
    uint32_t G[NX][2], a0[4], a1[4], a3[4];
    a0[0] = lds32(ke); a1[0] = lds32(ke + 32);
#pragma unroll
    for (int x = NX - 2; x >= 0; x -= 2) ldsm4(&G[x][0], ga + (X0 + x) * 256);
#pragma unroll
    for (int q = 1; q < 4; q++) { a0[q] = lds32(ke + 512 * q); a1[q] = lds32(ke + 512 * q + 32); }
#pragma unroll
    for (int q = 0; q < 4; q++) {
      a3[q] = a0[q] ^ zero;
#pragma unroll
      for (int o = 7; o >= 0; o--)
        if (O0 + o - q >= 0) mma16816(acc[o], a0[q], a1[q], am[q], a3[q], G[O0 + o - q - X0][0], G[O0 + o - q - X0][1]);
      am[q] = a1[q] ^ zero;
    }
    if (rho == 0) {
      const uint32_t b0 = lds32(ke + 512 * 4), b1 = lds32(ke + 520 * 4), bm = lds32(ke + 504 * 4), b3 = b0 ^ zero;
#pragma unroll
      for (int o = 7; o >= 0; o--)
        if (O0 + o - 4 >= 0) mma16816(acc[o], b0, b1, bm, b3, G[O0 + o - 4 - X0][0], G[O0 + o - 4 - X0][1]);
    }
    if (rho == 7 || (HI && rho == 0)) {
      const uint32_t nk = (lds32(tab + (kKeWords + kCWords + 7) * 4) & 0xffffu) ^ 0x8000u;
      const int d = g - 2 * t;
      const uint32_t wp = (d == 4 || d == 5 ? nk : 0u) | (d == 5 || d == 6 ? nk << 16 : 0u);
      const uint32_t wn = (d == -4 || d == -3 ? nk : 0u) | (d == -3 || d == -2 ? nk << 16 : 0u);
      if (HI) {
        const uint32_t f0 = rho ? 0u : wn, f1 = rho ? wp : 0u, f2 = rho ? 0u : wp, f3 = f0 ^ zero;
        const uint32_t fa = ga + (rho ? 256 : 0);
        uint32_t F[8][2];
#pragma unroll
        for (int x = 0; x < 8; x += 2) ldsm4(&F[x][0], fa + x * 256);
#pragma unroll
        for (int o = 0; o < 8; o++) mma16816(acc[o], f0, f1, f2, f3, F[o][0], F[o][1]);
      } else {
        mma16816(acc[7], 0u, wp, 0u, 0u, G[0][0], G[0][1]);
      }
    }
    ke += 64;
    lin -= 32;
  }

  mbar_wait(sb + aBar + 16, 0);
  if (NOTRIG == 4 && HI) asm volatile("griddepcontrol.launch_dependents;");
  {
    const uint32_t q4 = sb + aQ + slot * kQCh + kQ4Pad * 4;
    uint32_t off[4], B[10][2];
#pragma unroll
    for (int i = 0; i < 4; i++) {
      const int w = g - 8 * t + (i & 1) * 8 - (i >> 1) * 32;
      off[i] = q4 + (w ^ ((w >> 3) & 4)) * 4;
    }
    const uint32_t cb = tab + (kKeWords + 2 * g + t) * 4;
#pragma unroll
    for (int ks = 0; ks < (HI ? 10 : 9); ks++) { B[ks][0] = lds32(cb + ks * 32); B[ks][1] = lds32(cb + ks * 32 + 16); }
#pragma unroll
    for (int it = 0; it < (HI ? 24 : 9); it++) {
      const int tau = HI ? ((it & 1) ? 13 + it / 2 : 1 + it / 2) : ((it & 1) ? 8 - it / 2 : it / 2);
      uint32_t a[4];
#pragma unroll
      for (int i = 0; i < 4; i++) a[i] = lds32(off[i] + tau * 256);
#pragma unroll
      for (int o = 0; o < 8; o++) {
        const int ks = 2 * (O0 + o) - 6 - tau;
        if (ks >= 0 && ks < 10) mma16816(acc[o], a[0], a[1], a[2], a[3], B[ks][0], B[ks][1]);
      }
    }
  }
  if (NOTRIG == 2 && HI) asm volatile("griddepcontrol.launch_dependents;");
  {
    const uint32_t q8 = sb + aQ + slot * kQCh + (kQ4Words + kQ8Pad) * 4;
    uint32_t off[4], B[9][2];
#pragma unroll
    for (int i = 0; i < 4; i++) {
      const int w = g - 16 - 16 * t + (i & 1) * 8 - (i >> 1) * 64;
      off[i] = q8 + (w ^ (((w >> 5) & 1) * 12)) * 4;
    }
    const uint32_t cb = tab + (kKeWords + kCWords + g + t) * 4;
#pragma unroll
    for (int ks = 0; ks < (HI ? 9 : 1); ks++) { B[ks][0] = lds32(cb + ks * 32); B[ks][1] = lds32(cb + ks * 32 + 16); }
#pragma unroll
    for (int it = 0; it <= (HI ? 8 : 0); it++) {
      const int tau = (it & 1) ? 8 - it / 2 : it / 2;
      uint32_t a[4];
#pragma unroll
      for (int i = 0; i < 4; i++) a[i] = lds32(off[i] + tau * 512);
#pragma unroll
      for (int o = 0; o < 8; o++) {
        const int ks = O0 + o - 7 - tau;
        if (ks >= 0 && ks < 9) mma16816(acc[o], a[0], a[1], a[2], a[3], B[ks][0], B[ks][1]);
      }
    }
  }
  if (NOTRIG == 3 && HI) asm volatile("griddepcontrol.launch_dependents;");

  mbar_wait(sb + aBar + 8, 0);
  const uint32_t xa = sb + aX + slot * 4096 + O0 * 256;
  const uint32_t sa = xa + (lane >> 4) * 256 + (lane & 7) * 32 + ((((lane >> 3) ^ (lane >> 2)) & 1) << 4);
  uint32_t xf[16];
#pragma unroll
  for (int o = 0; o < 8; o += 2) ldsm4t(&xf[2 * o], sa + o * 256);
#pragma unroll
  for (int k = 0; k < 16; k++) {
    const float* a = &acc[k >> 1][(k & 1) * 2];
    xf[k] = pack_bf16(a[0] + bf_lo(xf[k]), a[1] + bf_hi(xf[k]));
  }
#pragma unroll
  for (int o = 0; o < 8; o += 2) stsm4t(sa + o * 256, xf[2 * o], xf[2 * o + 1], xf[2 * o + 2], xf[2 * o + 3]);
  __syncwarp();
  if (NOTRIG == 6 && HI) asm volatile("griddepcontrol.launch_dependents;");
  uint4* dst = (uint4*)g_hT + ((size_t)(O0 * 2 + (lane >> 3)) * kD + ch) * 8 + ((lane ^ (lane >> 3 & 1) ^ ch) & 7);
#pragma unroll
  for (int i = 0; i < 4; i++) lds128(&xf[4 * i], xa + i * 512 + lane * 16);
#pragma unroll
  for (int i = 0; i < 4; i++) stg128(dst + i * 4 * kD * 8, &xf[4 * i]);
  if (NOTRIG == 5 && HI) asm volatile("griddepcontrol.launch_dependents;");
}

template <bool BOTH>
__device__ __forceinline__ void box_job(uint32_t sb, int slot, int c) {
  const uint32_t ua = sb + aU + slot * kUCh + kUPad + c * 16;
  uint32_t v[16];
#pragma unroll
  for (int k = BOTH ? 0 : 1; k < 4; k++) {
    const uint32_t l = ua + (k - 2) * 16;
    lds128(&v[4 * k], l ^ ((l >> 3) & 16));
  }
  constexpr int lo = BOTH ? 5 : 11, hi = BOTH ? 28 : 26;
  float P[29];
  P[lo] = 0.f;
#pragma unroll
  for (int k = lo; k < hi; k++) P[k + 1] = P[k] + ((k & 1) ? bf_hi(v[k >> 1]) : bf_lo(v[k >> 1]));
  const uint32_t odd = (c << 2) & 16;
  uint32_t w[8];
#pragma unroll
  for (int i = 0; i < 8; i++) w[i] = pack_bf16(P[16 + i + 3] - P[16 + i - 2], P[16 + i - 2] - P[16 + i - 5]);
  const uint32_t q4 = (sb + aQ + slot * kQCh + kQ4Pad * 4 + c * 32) ^ odd;
  sts128(q4, w);
  sts128(q4 ^ 16, w + 4);
  if (BOTH) {
#pragma unroll
    for (int i = 0; i < 8; i++) w[i] = pack_bf16(P[16 + i + 5] - P[16 + i - 4], P[16 + i - 4] - P[16 + i - 11]);
    const uint32_t q8 = (q4 + (kQ4Words + kQ8Pad - kQ4Pad) * 4) ^ (odd << 1);
    sts128(q8, w);
    sts128(q8 ^ 16, w + 4);
  }
}

struct SsmArgs {
  const __nv_bfloat16 *x, *are, *aim, *bre, *bim, *cre, *cim, *ldt, *dsk;
  const char *w1, *w3;
  uint32_t zero;
};

__device__ __forceinline__ void put2(uint32_t a, const Cx& u, const Cx& v) { sts64(a, pack_bf16(u.r, u.i), pack_bf16(v.r, v.i)); }

__device__ __forceinline__ void helper_jobs(uint32_t sb, int b, int warp, int lane) {
  const unsigned long long nh = (b & 1) ? 0x030013411340ull : 0x140024112410ull;
  const unsigned long long nl = 0x110011111111ull;
  const int sh = 4 * (warp - 12);
  const unsigned long long below = (1ull << sh) - 1;
  const unsigned long long hb = nh & below;
  int job = __popcll(hb & 0x111111111111ull) + 2 * __popcll(hb & 0x222222222222ull) + 4 * __popcll(hb & 0x444444444444ull);
  if (warp == 12) {
    const uint32_t zz[4] = {0, 0, 0, 0};
#pragma unroll 1
    for (int s = 0; s < 5; s++) {
      const uint32_t qb = sb + aQ + s * kQCh;
      if (lane < 22) sts128(qb + (lane < 14 ? 16 * lane : (kQ4Pad + 1536) * 4 + 16 * (lane - 14)), zz);
      if (lane < 30) sts128(qb + kQ4Words * 4 + ((16 * lane) ^ ((lane & 8) * 6)), zz);
    }
  }
#pragma unroll 1
  for (int n = (int)((nh >> sh) & 15) + (warp == 12); n > 0; n--, job++)
    box_job<true>(sb, warp == 12 ? min(lane, 4) : job >> 2, warp == 12 ? -1 : (job & 3) * 32 + lane);
  const int jl = __popcll(nl & below);
  box_job<false>(sb, jl >> 1, 128 + (jl & 1) * 32 + lane);
  __syncwarp();
  if (lane == 0) mbar_arrive(sb + aBar + 16);
}

template <int A, int B>
__device__ __forceinline__ void r_rows(uint32_t fa, Cx (&S)[2][4], const Cx (&zb)[2]) {
#pragma unroll
  for (int j = A; j < B; j++) {
    put2(fa + j * kFacRow, S[0][j & 1], S[1][j & 1]);
#pragma unroll
    for (int m = 0; m < 2; m++)
      if (j < 30) S[m][j & 1] = j == 0 ? zb[m] : cmul(S[m][j & 1], zb[m]);
  }
}
template <int A, int B>
__device__ __forceinline__ void l_rows(uint32_t fl, Cx (&S)[2][4], const Cx (&za)[2], const Cx (&zb)[2]) {
#pragma unroll
  for (int k = A; k < B; k++) {
    if (k < 4) {
      put2(fl + 2 * k * kFacRow, S[0][k], S[1][k]);
      put2(fl + (2 * k + 1) * kFacRow, cmul(S[0][k], za[0]), cmul(S[1][k], za[1]));
      S[0][k] = cmul(S[0][k], zb[0]); S[1][k] = cmul(S[1][k], zb[1]);
      put2(fl + (8 + k) * kFacRow, S[0][k], S[1][k]);
      if (k == 3) put2(fl + 21 * kFacRow, cmul(S[0][3], csqr(za[0])), cmul(S[1][3], csqr(za[1])));
    } else {
      S[0][0] = cmul(S[0][0], zb[0]); S[1][0] = cmul(S[1][0], zb[1]);
      put2(fl + (k < 6 ? 4 + 2 * k : 10 + k) * kFacRow, S[0][0], S[1][0]);
      if (k < 6) {
        S[0][2] = cmul(S[0][2], zb[0]); S[1][2] = cmul(S[1][2], zb[1]);
        put2(fl + (5 + 2 * k) * kFacRow, S[0][2], S[1][2]);
      }
    }
  }
}

__global__ void __launch_bounds__(kSsmThreads, 1) ssm_kernel(const SsmArgs a) {
  extern __shared__ __align__(1024) unsigned char smem_raw[];
  const uint32_t sb = smem_u32(smem_raw);
  const int b = blockIdx.x, tid = threadIdx.x;
  const int warp = __shfl_sync(0xffffffffu, tid >> 5, 0), lane = tid & 31;
  if (!NOTRIG) asm volatile("griddepcontrol.launch_dependents;");
  const uint32_t la = sb + (((lane >> 1) & 1) * 8 + 2 * (lane >> 3) + (lane & 1)) * kLnRow + ((lane >> 1) & 1) * 64 + ((lane >> 2) & 1) * 32;
  const uint32_t go = (((lane >> 2) + (lane & 2) * 8) * 128 + b) * 2 + ((lane ^ (b >> 2)) & 1);

  if (warp < 20) {
  const int slot = warp >> 2, role = (warp + slot) & 3, ch = slot_channel(b, slot);
  const int pi = ch * kN + (role >> 1) * 64 + lane * 2;
  const uint32_t ldt = ldg16(a.ldt + ch), are = ldg32(a.are + pi), aim = ldg32(a.aim + pi);
  uint32_t bre, bim, cre, cim;
  if (L1 >= 0) { bre = ldg32(a.bre + pi); bim = ldg32(a.bim + pi); cre = ldg32(a.cre + pi); cim = ldg32(a.cim + pi); }
  uint32_t xv[9];
  {
    const uint32_t* xr = (const uint32_t*)(a.x + (size_t)(b * 16 + (warp & 15)) * kD) + lane;
#pragma unroll
    for (int i = 0; i < 9; i++)
      asm volatile("{\n.reg .pred p;\nsetp.lt.s32 p, %2, 16;\n@p ld.volatile.global.u32 %0, [%1];\n}\n" : "=r"(xv[i]) : "l"(xr + i * 32), "r"(warp) : "memory");
  }
  if (L1 < 0) { bre = ldg32(a.bre + pi); bim = ldg32(a.bim + pi); cre = ldg32(a.cre + pi); cim = ldg32(a.cim + pi); }
  const uint32_t dsk = ldg16(a.dsk + ch);

  const uint32_t fac = sb + aFac + (slot * 2 + (role >> 1)) * kFacHalf;
  const uint32_t fa = fac + lane * 8 + (role & 1) * 32 * kFacRow;
  Cx za[2], zb[2], S[2][4];
  const float dt = round_bf16(expf(bf_lo(ldt)));
  auto l_init = [&]() {
#pragma unroll
    for (int m = 0; m < 2; m++) {
      const Cx z2 = csqr(za[m]), z4 = csqr(z2);
      const Cx c = {m ? bf_hi(cre) : bf_lo(cre), -(m ? bf_hi(cim) : bf_lo(cim))};
      const Cx d = {dt * (m ? bf_hi(bre) : bf_lo(bre)), -dt * (m ? bf_hi(bim) : bf_lo(bim))};
      S[m][0] = cmul(c, d); S[m][1] = cmul(S[m][0], z2); S[m][2] = cmul(S[m][0], z4); S[m][3] = cmul(S[m][1], z4);
    }
  };
  {
    const float kr = dt * 1.4426950408889634f, ki = dt * ((role & 1) ? -0.15915494309189535f : 0.15915494309189535f);
    const float ea = (role & 1) ? 1.f : 8.f, eb = (role & 1) ? 256.f : 16.f;
#pragma unroll
    for (int m = 0; m < 2; m++) {
      const float lr = (m ? bf_hi(are) : bf_lo(are)) * kr, tn = (m ? bf_hi(aim) : bf_lo(aim)) * ki;
      za[m] = cexp_scaled(lr, tn, ea); zb[m] = cexp_scaled(lr, tn, eb);
    }
#pragma unroll
    for (int m = 0; m < 2; m++) { S[m][0] = {1.f, 0.f}; S[m][1] = S[m][2] = S[m][3] = za[m]; }
    if (role & 1) {
      if (L1 >= 0) { l_init(); l_rows<0, (L1 > 0 ? L1 : 0)>(fa, S, za, zb); }
    } else {
      r_rows<0, J1>(fa, S, zb);
    }
  }

  if (warp < 16) {
    const uint32_t ra = sb + warp * kLnRow + (warp >> 3) * 64 + lane * 4;
    float s = 0.f, q = 0.f;
    const float x0 = bf_lo(__shfl_sync(0xffffffffu, xv[0], 0));
#pragma unroll
    for (int i = 0; i < 9; i++) {
      const float lo = bf_lo(xv[i]) - x0, hi = bf_hi(xv[i]) - x0;
      s += lo + hi;
      q = fmaf(lo, lo, fmaf(hi, hi, q));
    }
#pragma unroll
    for (int m = 16; m; m >>= 1) {
      s += __shfl_xor_sync(0xffffffffu, s, m); q += __shfl_xor_sync(0xffffffffu, q, m);
    }
#pragma unroll
    for (int i = 0; i < 9; i++) sts32(ra + aX + i * 128, xv[i]);
    const float dm = s * (1.f / kD), mean = x0 + dm, var = fmaxf(q * (1.f / kD) - dm * dm, 0.f);
    float sd;
    asm("sqrt.approx.f32 %0, %1;" : "=f"(sd) : "f"(round_bf16(round_bf16(var) + 1e-5f)));
    const float r = rcpf(round_bf16(sd));
    const uint32_t mm = pack_bf16(mean, mean);
#pragma unroll
    for (int i = 0; i < 9; i++) {
      const uint32_t d = sub_bf16x2(xv[i], mm);
      sts32(ra + aU + i * 128, pack_bf16(bf_lo(d) * r, bf_hi(d) * r));
    }
  }
  if (warp < 16) bar_arrive(10, 512 + 32);
  bar_sync(9, 640 + 64);
  {
    uint32_t v[2][4];
    const uint32_t l = la + aU + (warp >> 1) * 64 + (warp & 1) * 16;
    uint4* dst = g_uT + go + ((warp >> 1) * 32 + (warp & 1) * 8) * 256;
    ldsm4t(v[0], l);
    if (warp < 16) ldsm4t(v[1], l + 640);
    stg128(dst, v[0]);
    if (warp < 16) stg128(dst + 320 * 256, v[1]);
  }
  bar_arrive(6, 640 + 32);
  if (role & 1) {
    if (L1 < 0) l_init();
    l_rows<(L1 > 0 ? L1 : 0), 11>(fa, S, za, zb);
    if (EG) bar_arrive(11 + slot, 128);
    bar_sync(1 + slot, 128);
  } else {
    r_rows<J1, (J1 > 16 ? J1 : 16)>(fa, S, zb);
    if (EG) bar_arrive(1 + slot, 128);
    r_rows<(J1 > 16 ? J1 : 16), 32>(fa, S, zb);
    bar_sync((EG ? 11 : 1) + slot, 128);
  }
  {
    const int mt = ~role & 1;
    const bool up = role >> 1;
    float c[3][4];
#pragma unroll
    for (int n = 0; n < 3; n++) c[n][0] = c[n][1] = c[n][2] = c[n][3] = 0.f;
    const uint32_t aa = fac + (mt * 16 + (lane & 15)) * kFacRow + (lane >> 4) * 16;
    const uint32_t ba = fac + (32 + (lane & 7)) * kFacRow + (lane >> 3) * 16;
#pragma unroll
    for (int k2 = 0; k2 < 4; k2++) {
      uint32_t av[2][4], bv[3][4];
      ldsm4(av[0], aa + k2 * 64); ldsm4(av[1], aa + k2 * 64 + 32);
#pragma unroll
      for (int n = 0; n < 3; n++) ldsm4(bv[n], ba + n * 8 * kFacRow + k2 * 64);
#pragma unroll
      for (int h = 0; h < 2; h++)
#pragma unroll
        for (int n = 0; n < 3; n++) mma16816(c[n], av[h][0], av[h][1], av[h][2], av[h][3], bv[n][2 * h], bv[n][2 * h + 1]);
    }
    const uint32_t ex = fac + mt * 16 * kFacRow + lane * 8;
#pragma unroll
    for (int n = 0; n < 3; n++) sts64(ex + n * 256, __float_as_uint(up ? c[n][0] : c[n][2]), __float_as_uint(up ? c[n][1] : c[n][3]));
    if (EG) bar_sync((mt ? 11 : 1) + slot, 64); else bar_sync(1 + slot, 128);
    float v0[3], v1[3];
#pragma unroll
    for (int n = 0; n < 3; n++) {
      asm volatile("ld.shared.v2.f32 {%0, %1}, [%2];" : "=f"(v0[n]), "=f"(v1[n]) : "r"(ex + (up ? -kFacHalf : kFacHalf) + n * 256) : "memory");
      v0[n] += up ? c[n][2] : c[n][0];
      v1[n] += up ? c[n][3] : c[n][1];
    }
    const int j = mt * 16 + (role >> 1) * 8 + (lane >> 2), t = lane & 3;
    const uint32_t tab = sb + aTab + slot * kTabCh;
    const float k512 = __shfl_down_sync(0xffffffffu, v1[2], 1);
    if (j + t == 0) v0[0] += bf_lo(dsk);
    if (j == 31 && t == 1) v1[1] -= k512;
    const uint32_t w0 = pack_bf16(v1[0], v0[0]), w1 = pack_bf16(v0[1], v1[1]), w2 = pack_bf16(v0[2], v1[2]);
    const uint32_t k0 = tab + (16 + 8 * j + 2 * t) * 4;
    sts16(k0, w0 >> 16); sts32(k0 + 4, w0); sts16(k0 + 10, w0);
    if (t < 2) {
      const uint32_t k1 = tab + (16 + 256 + 8 * j + 4 * t) * 4;
      if (j + t) { sts16(k1 - 4, w1); sts16(k1 + 2, w1); }
      sts16(k1, w1);
      sts32(k1 + 4, __byte_perm(w1, 0, 0x1010));
      sts32(k1 + 8, __byte_perm(w1, 0, 0x1032));
      sts16(k1 + 14, w1 >> 16);
    } else {
      sts32(tab + (kKeWords + 16 + 32 * (t - 2) + j) * 4, w1);
    }
    const uint32_t k2 = tab + (kKeWords + kCWords + 7) * 4 + (64 * t + j) * 2;
    if (t < 2 || (t == 2 && j == 0)) sts16(k2, w2);
    if (t < 2) sts16(k2 + 64, w2 >> 16);
  }
  }

  if (warp < 12) {
    bar_sync(8, kSsmThreads);
    if (SMR) asm volatile("setmaxnreg.inc.sync.aligned.u32 96;");
    const unsigned long long map = (b & 1) ? 0x4fff31092ba8ull : 0x3fff20b91ca8ull;
    const int code = (int)((map >> (4 * warp)) & 15), s = code & 7, c = slot_channel(b, s);
    if (code != 15) {
      mbar_wait(sb + aBar, 0);
      if (code & 8) conv_unit<true>(sb, s, c, warp, lane, a.zero);
      else conv_unit<false>(sb, s, c, warp, lane, a.zero);
    }
  } else {
    if (SMR) asm volatile("setmaxnreg.dec.sync.aligned.u32 64;");
    const uint32_t z[4] = {0, 0, 0, 0};
    if (warp == 20 || warp == 21) {
      const int k = warp - 20;
      const uint32_t bar = sb + aBar + k * 8, reg = sb + (k ? aX : aU);
      const bool lead = elect_one();
      if (lead) {
        mbar_init(bar, 1);
        if (k) mbar_init(sb + aBar + 16, 10);
        asm volatile("fence.mbarrier_init.release.cluster;" ::: "memory");
        mbar_expect(bar, 5 * 4096);
        if (b + k == 0) g_epoch++;
      }
      if (k) {
        bar_arrive(8, kSsmThreads);
        bar_sync(10, 512 + 32);
        bar_sync(7, 64);
#pragma unroll 1
        for (int i = 0; i < 6; i++) {
          uint32_t v[6][4];
#pragma unroll
          for (int j = 0; j < 6; j++) ldsm4t(v[j], la + aX + i * 192 + (j >> 1) * 64 + (j & 1) * 16);
#pragma unroll
          for (int j = 0; j < 6; j++) stg128(g_xT + go + (i * 96 + (j >> 1) * 32 + (j & 1) * 8) * 256, v[j]);
        }
        __syncwarp();
      } else {
        bar_sync(6, 640 + 32);
      }
      if (lane < NREP) asm volatile("fence.acq_rel.gpu;\nred.relaxed.gpu.global.add.u32 [%0], 1;" ::"l"(&g_lncnt[(k * 32 + lane) * 64]) : "memory");
      if (!k) {
        if (lane < 16) {
#pragma unroll
          for (int s = 0; s < 5; s++) sts128(reg + s * kUCh + lane * 16, z);
        }
        bar_arrive(8, kSsmThreads);
      }
      if (lead) {
        asm volatile("fence.proxy.async.shared::cta;" ::: "memory");
        flag_wait(&g_lncnt[(k * 32 + (b & (NREP - 1))) * 64], 128);
        asm volatile("fence.proxy.async.global;" ::: "memory");
#pragma unroll
        for (int s = 0; s < 5; s++)
          bulk_g2s(reg + (k ? s * 4096 : s * kUCh + kUPad), (k ? g_xT : g_uT) + (size_t)slot_channel(b, s) * 256, 4096, bar);
      }
      __syncwarp();
      if (!k) {
        bar_arrive(7, 64);
#pragma unroll 1
        for (int p = 0; p < kAhead; p++) {
          prefetch_pass(a.w1, a.w3, nullptr, p, b >> 4, (b & 15) * 36 + lane);
          if (lane < 4) prefetch_pass(a.w1, a.w3, nullptr, p, b >> 4, (b & 15) * 36 + 32 + lane);
        }
      }
    } else {
      if (warp >= 22) {
#pragma unroll 1
        for (int i = tid - 704; i < 5 * kTabCh / 16; i += 64) sts128(sb + aTab + i * 16, z);
        bar_arrive(9, 640 + 64);
      }
      bar_sync(8, kSsmThreads);
      mbar_wait(sb + aBar, 0);
      helper_jobs(sb, b, warp, lane);
    }
  }
}

typedef CUresult (*EncodeFn)(CUtensorMap*, CUtensorMapDataType, cuuint32_t, void*, const cuuint64_t*, const cuuint64_t*,
                             const cuuint32_t*, const cuuint32_t*, CUtensorMapInterleave, CUtensorMapSwizzle,
                             CUtensorMapL2promotion, CUtensorMapFloatOOBfill);

void encode2d(EncodeFn fn, CUtensorMap* tm, void* p, int cols, int rows, int bx, int by) {
  cuuint64_t gd[2] = {(cuuint64_t)cols, (cuuint64_t)rows}, gs[1] = {(cuuint64_t)cols * 2};
  cuuint32_t box[2] = {(cuuint32_t)bx, (cuuint32_t)by}, es[2] = {1, 1};
  fn(tm, CU_TENSOR_MAP_DATA_TYPE_BFLOAT16, 2, p, gd, gs, box, es, CU_TENSOR_MAP_INTERLEAVE_NONE, CU_TENSOR_MAP_SWIZZLE_128B,
     CU_TENSOR_MAP_L2_PROMOTION_L2_128B, CU_TENSOR_MAP_FLOAT_OOB_FILL_NONE);
}

}

extern "C" void kernel_launch(void* const* d_in, const int* in_sizes, int n_in, void* d_out, int out_size) {
  typedef const __nv_bfloat16* P;
  void* fn = nullptr;
  cudaDriverEntryPointQueryResult qr;
  cudaGetDriverEntryPoint("cuTensorMapEncodeTiled", &fn, cudaEnableDefault, &qr);
  CUtensorMap t1, t3, t2;
  encode2d((EncodeFn)fn, &t1, d_in[10], kF, kD, 64, kBoxRows);
  encode2d((EncodeFn)fn, &t3, d_in[11], kF, kD, 64, kBoxRows);
  encode2d((EncodeFn)fn, &t2, d_in[12], kD, kF, 64, kBoxRows);
  cudaFuncSetAttribute(ffn_kernel, cudaFuncAttributeMaxDynamicSharedMemorySize, kFfnSmem);

  cudaFuncSetAttribute(ssm_kernel, cudaFuncAttributeMaxDynamicSharedMemorySize, kSsmSmem);
  SsmArgs sa = {(P)d_in[0], (P)d_in[1], (P)d_in[2], (P)d_in[3], (P)d_in[4], (P)d_in[5], (P)d_in[6], (P)d_in[7], (P)d_in[8],
                (const char*)d_in[10], (const char*)d_in[11], 0u};
  ssm_kernel<<<128, kSsmThreads, kSsmSmem, cudaStreamPerThread>>>(sa);

  cudaLaunchConfig_t cfg = {};
  cfg.gridDim = dim3(128);
  cfg.blockDim = dim3(384);
  cfg.dynamicSmemBytes = kFfnSmem;
  cfg.stream = cudaStreamPerThread;
  cudaLaunchAttribute at[1];
  at[0].id = cudaLaunchAttributeProgrammaticStreamSerialization;
  at[0].val.programmaticStreamSerializationAllowed = 1;
  cfg.attrs = at;
  cfg.numAttrs = NOPDL ? 0 : 1;
  cudaLaunchKernelEx(&cfg, ffn_kernel, t1, t3, t2, (__nv_bfloat16*)d_out, 1);
}
```

```cpp
#include <cuda_runtime.h>
#include <cuda_bf16.h>
#include <cuda.h>
#include <stdint.h>

namespace {

constexpr int kL = 2048, kD = 576, kF = 4608, kN = 128;
constexpr int kSpinLimit = 100000;

}

__device__ __align__(128) uint4 g_uT[kD * 256];
__device__ __align__(128) uint4 g_xT[kD * 256];
__device__ unsigned g_cnt[2 * 64];
__device__ __align__(1024) __nv_bfloat16 g_hT[kD * kL];
__device__ uint4 g_part[16 * 9 * 8 * 1024];
__device__ unsigned g_epoch;


namespace {

__device__ __forceinline__ uint32_t smem_u32(const void* p) { return (uint32_t)__cvta_generic_to_shared(p); }
__device__ __forceinline__ void mbar_init(uint32_t b, int c) {
  asm volatile("mbarrier.init.shared::cta.b64 [%0], %1;" ::"r"(b), "r"(c));
}
__device__ __forceinline__ void mbar_expect(uint32_t b, int bytes) {
  asm volatile("mbarrier.arrive.expect_tx.shared::cta.b64 _, [%0], %1;" ::"r"(b), "r"(bytes) : "memory");
}
__device__ __forceinline__ void mbar_arrive(uint32_t b) {
  asm volatile("mbarrier.arrive.shared::cta.b64 _, [%0];" ::"r"(b) : "memory");
}
__device__ __forceinline__ void mbar_arrive_cluster(uint32_t b) {
  asm volatile("mbarrier.arrive.shared::cluster.b64 _, [%0];" ::"r"(b) : "memory");
}
__device__ __forceinline__ bool elect_one() {
  uint32_t p;
  asm volatile("{\n.reg .pred q;\nelect.sync _|q, 0xffffffff;\nselp.u32 %0, 1, 0, q;\n}\n" : "=r"(p));
  return p;
}
__device__ __forceinline__ uint32_t mapa(uint32_t a, uint32_t rank) {
  uint32_t r;
  asm volatile("mapa.shared::cluster.u32 %0, %1, %2;" : "=r"(r) : "r"(a), "r"(rank));
  return r;
}
__device__ __forceinline__ void mbar_wait(uint32_t b, uint32_t parity) {
  asm volatile(
      "{\n.reg .pred p;\n.reg .u32 n;\n"
      "mbarrier.try_wait.parity.shared::cta.b64 p, [%0], %1;\n"
      "@p bra DONE;\n"
      "mov.u32 n, 0;\n"
      "LOOP:\n"
      "mbarrier.try_wait.parity.shared::cta.b64 p, [%0], %1;\n"
      "@p bra DONE;\n"
      "add.u32 n, n, 1;\n"
      "setp.lt.u32 p, n, 1000000;\n"
      "@p bra LOOP;\n"
      "trap;\n"
      "DONE:\n}\n" ::"r"(b), "r"(parity) : "memory");
}
__device__ __forceinline__ void flag_wait(const unsigned* p, unsigned target) {
  unsigned v;
#pragma unroll 1
  for (int it = 0; it < 10 * kSpinLimit; it++) {
    asm volatile("ld.acquire.gpu.global.u32 %0, [%1];" : "=r"(v) : "l"(p) : "memory");
    if (v >= target) return;
  }
  asm volatile("trap;");
}
__device__ __forceinline__ void tma2d(uint32_t dst, const CUtensorMap* tm, uint32_t bar, int x, int y) {
  asm volatile("cp.async.bulk.tensor.2d.shared::cluster.global.mbarrier::complete_tx::bytes [%0], [%1, {%3, %4}], [%2];"
               ::"r"(dst), "l"(tm), "r"(bar), "r"(x), "r"(y) : "memory");
}
__device__ __forceinline__ void tma2d_mc(uint32_t dst, const CUtensorMap* tm, uint32_t bar, int x, int y) {
  asm volatile("cp.async.bulk.tensor.2d.shared::cluster.global.mbarrier::complete_tx::bytes.multicast::cluster [%0], [%1, {%3, %4}], [%2], %5;"
               ::"r"(dst), "l"(tm), "r"(bar), "r"(x), "r"(y), "h"((uint16_t)3) : "memory");
}
__device__ __forceinline__ void tma_prefetch(const CUtensorMap* tm, int x, int y) {
  asm volatile("cp.async.bulk.prefetch.tensor.2d.L2.global [%0, {%1, %2}];" ::"l"(tm), "r"(x), "r"(y) : "memory");
}
__device__ __forceinline__ void bulk_g2s(uint32_t dst, const void* src, int bytes, uint32_t bar) {
  asm volatile("cp.async.bulk.shared::cluster.global.mbarrier::complete_tx::bytes [%0], [%1], %2, [%3];"
               ::"r"(dst), "l"(src), "r"(bytes), "r"(bar) : "memory");
}
__device__ __forceinline__ void ldsm4t(uint32_t* r, uint32_t a) {
  asm volatile("ldmatrix.sync.aligned.m8n8.x4.trans.shared.b16 {%0,%1,%2,%3}, [%4];"
               : "=r"(r[0]), "=r"(r[1]), "=r"(r[2]), "=r"(r[3]) : "r"(a) : "memory");
}
__device__ __forceinline__ void stsm4(uint32_t a, uint32_t r0, uint32_t r1, uint32_t r2, uint32_t r3) {
  asm volatile("stmatrix.sync.aligned.m8n8.x4.shared.b16 [%0], {%1,%2,%3,%4};" ::"r"(a), "r"(r0), "r"(r1), "r"(r2), "r"(r3) : "memory");
}
__device__ __forceinline__ void lds128(uint32_t* r, uint32_t a) {
  asm volatile("ld.shared.v4.u32 {%0,%1,%2,%3}, [%4];" : "=r"(r[0]), "=r"(r[1]), "=r"(r[2]), "=r"(r[3]) : "r"(a) : "memory");
}
__device__ __forceinline__ void sts128(uint32_t a, const uint32_t* r) {
  asm volatile("st.shared.v4.u32 [%0], {%1,%2,%3,%4};" ::"r"(a), "r"(r[0]), "r"(r[1]), "r"(r[2]), "r"(r[3]) : "memory");
}
__device__ __forceinline__ void stg128(void* p, const uint32_t* r) {
  asm volatile("st.global.v4.u32 [%0], {%1,%2,%3,%4};" ::"l"(p), "r"(r[0]), "r"(r[1]), "r"(r[2]), "r"(r[3]) : "memory");
}
__device__ __forceinline__ uint32_t pack_bf16(float lo, float hi) {
  uint32_t r;
  asm("cvt.rn.bf16x2.f32 %0, %1, %2;" : "=r"(r) : "f"(hi), "f"(lo));
  return r;
}
__device__ __forceinline__ float bf_lo(uint32_t v) { return __uint_as_float(v << 16); }
__device__ __forceinline__ float bf_hi(uint32_t v) { return __uint_as_float(v & 0xffff0000u); }
__device__ __forceinline__ float round_bf16(float v) { return __bfloat162float(__float2bfloat16(v)); }
__device__ __forceinline__ uint32_t mul_bf16x2(uint32_t a, uint32_t b) {
  uint32_t r;
  asm("mul.rn.bf16x2 %0, %1, %2;" : "=r"(r) : "r"(a), "r"(b));
  return r;
}
__device__ __forceinline__ uint32_t sub_bf16x2(uint32_t a, uint32_t b) {
  uint32_t r;
  asm("sub.rn.bf16x2 %0, %1, %2;" : "=r"(r) : "r"(a), "r"(b));
  return r;
}
__device__ __forceinline__ float ex2f(float x) { float r; asm("ex2.approx.ftz.f32 %0, %1;" : "=f"(r) : "f"(x)); return r; }
__device__ __forceinline__ float rcpf(float x) { float r; asm("rcp.approx.ftz.f32 %0, %1;" : "=f"(r) : "f"(x)); return r; }

#define ACC32(c, d)                                                                                        \
  c(d[0]), c(d[1]), c(d[2]), c(d[3]), c(d[4]), c(d[5]), c(d[6]), c(d[7]), c(d[8]), c(d[9]), c(d[10]),      \
      c(d[11]), c(d[12]), c(d[13]), c(d[14]), c(d[15]), c(d[16]), c(d[17]), c(d[18]), c(d[19]), c(d[20]),  \
      c(d[21]), c(d[22]), c(d[23]), c(d[24]), c(d[25]), c(d[26]), c(d[27]), c(d[28]), c(d[29]), c(d[30]), c(d[31])
#define REGS32                                                                                             \
  "{%0,%1,%2,%3,%4,%5,%6,%7,%8,%9,%10,%11,%12,%13,%14,%15,%16,%17,%18,%19,%20,%21,%22,%23,%24,%25,%26,%27,%28,%29,%30,%31}"

template <bool FIRST, int OFF>
__device__ __forceinline__ void wgmma64(float (&d)[32], const uint32_t* a, uint32_t dlo) {
  if constexpr (FIRST) {
    asm volatile("{\n.reg .pred p;\n.reg .b32 t;\n.reg .b64 db;\nsetp.ne.b32 p, 0, 0;\nadd.u32 t, %36, %37;\nmov.b64 db, {t, 0x40000040};\n"
                 "wgmma.mma_async.sync.aligned.m64n64k16.f32.bf16.bf16 " REGS32 ", {%32,%33,%34,%35}, db, p, 1, 1, 1;\n}\n"
                 : ACC32("=f", d) : "r"(a[0]), "r"(a[1]), "r"(a[2]), "r"(a[3]), "r"(dlo), "n"(OFF));
  } else {
    asm volatile("{\n.reg .pred p;\n.reg .b32 t;\n.reg .b64 db;\nsetp.eq.b32 p, 0, 0;\nadd.u32 t, %36, %37;\nmov.b64 db, {t, 0x40000040};\n"
                 "wgmma.mma_async.sync.aligned.m64n64k16.f32.bf16.bf16 " REGS32 ", {%32,%33,%34,%35}, db, p, 1, 1, 1;\n}\n"
                 : ACC32("+f", d) : "r"(a[0]), "r"(a[1]), "r"(a[2]), "r"(a[3]), "r"(dlo), "n"(OFF));
  }
}
__device__ __forceinline__ void wg_fence() { asm volatile("wgmma.fence.sync.aligned;" ::: "memory"); }
__device__ __forceinline__ void wg_commit() { asm volatile("wgmma.commit_group.sync.aligned;" ::: "memory"); }
template <int N>
__device__ __forceinline__ void wg_wait() { asm volatile("wgmma.wait_group.sync.aligned %0;" ::"n"(N) : "memory"); }
__device__ __forceinline__ void pin(float& v) { asm volatile("" : "+f"(v)::"memory"); }
__device__ __forceinline__ void pin(uint32_t& v) { asm volatile("" : "+r"(v)::"memory"); }

constexpr int kSlotBytes = 12288, kPasses = 27, kBoxRows = 48;
constexpr uint32_t oR = 0, kRWg = 9 * 8192, oW = 2 * kRWg, oBar = oW + 6 * kSlotBytes;
constexpr uint32_t bFull = oBar, bEmpty = bFull + 48, bX = bEmpty + 48, bP0 = bX + 96, bTag = bP0 + 8,
                   oK = bTag + 8, oTag = oK + 256, oH8 = oTag + 16, oEnd = oH8 + 2048;
constexpr int kFfnSmem = oEnd;
static_assert(oH8 % 16 == 0 && kFfnSmem <= 232448, "smem");

__device__ __forceinline__ uint4* part_ptr(int mt, int blk, int slot) { return g_part + ((mt * 9 + blk) * 8 + slot) * 1024; }

struct Ctx {
  uint32_t sb;
  uint32_t relbar;
  bool rel;
  bool always;
  uint32_t priv;
  float c0, c1;
  uint32_t ready;
  uint32_t tag;
  const uint4* src;
  uint4* dst;
};

__device__ __forceinline__ uint32_t mbar_probe(uint32_t b, uint32_t parity) {
  uint32_t ok;
  asm volatile("{\n.reg .pred p;\nmbarrier.test_wait.parity.shared::cta.b64 p, [%1], %2;\nselp.u32 %0, 1, 0, p;\n}\n"
               : "=r"(ok) : "r"(b), "r"(parity) : "memory");
  return ok;
}
__device__ __forceinline__ uint32_t frag_addr(uint32_t sb, int w, int lane) {
  return sb + oR + (w >> 2) * kRWg + ((lane >> 4) * 8 + (lane & 7)) * 128 + (((2 * (w & 3) + ((lane >> 3) & 1)) ^ (lane & 7)) << 4);
}
__device__ __forceinline__ uint32_t frag_index() { return (threadIdx.x >> 5) * 128 + (threadIdx.x & 31); }
__device__ __forceinline__ void ldg_relaxed(uint32_t* v, const uint4* p) {
  asm volatile("{\n.reg .b128 t;\n.reg .b64 lo, hi;\nld.relaxed.gpu.global.b128 t, [%4];\nmov.b128 {lo, hi}, t;\nmov.b64 {%0, %1}, lo;\nmov.b64 {%2, %3}, hi;\n}\n"
               : "=r"(v[0]), "=r"(v[1]), "=r"(v[2]), "=r"(v[3]) : "l"(p) : "memory");
}
__device__ __forceinline__ void stg_relaxed(uint4* p, const uint32_t* v) {
  asm volatile("{\n.reg .b128 t;\n.reg .b64 lo, hi;\nmov.b64 lo, {%1, %2};\nmov.b64 hi, {%3, %4};\nmov.b128 t, {lo, hi};\nst.relaxed.gpu.global.b128 [%0], t;\n}\n"
               ::"l"(p), "r"(v[0]), "r"(v[1]), "r"(v[2]), "r"(v[3]) : "memory");
}
__device__ __forceinline__ void ensure_landed(uint32_t* v, const uint4* p, uint32_t tag) {
#pragma unroll 1
  for (int it = 0; it < kSpinLimit && ((v[0] ^ tag) & 1); it++) ldg_relaxed(v, p);
}
__device__ __forceinline__ void load_tile(uint32_t (&v)[16], const uint4* p) {
#pragma unroll
  for (int q = 0; q < 4; q++) ldg_relaxed(&v[4 * q], p + q * 32);
}
__device__ __forceinline__ void ensure_tile(uint32_t (&v)[16], const uint4* p, uint32_t tag) {
#pragma unroll 1
  for (int it = 0; it < kSpinLimit; it++) {
    const uint32_t m = (v[0] ^ tag) | (v[4] ^ tag) | (v[8] ^ tag) | (v[12] ^ tag);
    if (!__any_sync(0xffffffffu, m & 1)) break;
    load_tile(v, p);
  }
}
__device__ __forceinline__ uint32_t add_bf16x2(uint32_t a, uint32_t b) {
  uint32_t r;
  asm("add.rn.bf16x2 %0, %1, %2;" : "=r"(r) : "r"(a), "r"(b));
  return r;
}
template <int G>
__device__ __forceinline__ void centre_group(uint32_t (&A)[144], uint32_t m0, uint32_t m1) {
#pragma unroll
  for (int i = 24 * G; i < 24 * G + 24; i++) { A[i] = sub_bf16x2(A[i], (i & 1) ? m1 : m0); pin(A[i]); }
}
__device__ __forceinline__ void mma16816(float* d, uint32_t a0, uint32_t a1, uint32_t a2, uint32_t a3, uint32_t b0, uint32_t b1) {
  asm volatile("mma.sync.aligned.m16n8k16.row.col.f32.bf16.bf16.f32 {%0,%1,%2,%3}, {%4,%5,%6,%7}, {%8,%9}, {%0,%1,%2,%3};"
               : "+f"(d[0]), "+f"(d[1]), "+f"(d[2]), "+f"(d[3]) : "r"(a0), "r"(a1), "r"(a2), "r"(a3), "r"(b0), "r"(b1));
}
__device__ __forceinline__ void mma1688(float* d, uint32_t a0, uint32_t a1, uint32_t b0) {
  asm volatile("mma.sync.aligned.m16n8k8.row.col.f32.bf16.bf16.f32 {%0,%1,%2,%3}, {%4,%5}, {%6}, {%0,%1,%2,%3};"
               : "+f"(d[0]), "+f"(d[1]), "+f"(d[2]), "+f"(d[3]) : "r"(a0), "r"(a1), "r"(b0));
}
template <typename T>
__device__ __forceinline__ void pinp(T*& v) { asm volatile("" : "+l"(v)::"memory"); }

constexpr int kAhead = 3;

enum Kind { K_FIRST, K_GATE, K_UP, K_XCHG };

template <int KIND, int S>
__device__ __forceinline__ void epi_slice(Ctx& c, uint32_t (&A)[144], float (&p)[32], uint32_t (&Sv)[16], int n, int mt, int f) {
  if constexpr (KIND == K_FIRST) {
    if (c.always) {
      if constexpr (S < 5) centre_group<S + 1>(A, Sv[0], Sv[1]);
      if (S == 1) {
        const float e0 = __uint_as_float(Sv[2]), e1 = __uint_as_float(Sv[3]);
        uint32_t v = pack_bf16(fmaxf(c.c0 * (1.f / kD) - e0 * e0, 0.f), fmaxf(c.c1 * (1.f / kD) - e1 * e1, 0.f));
        v = pack_bf16(bf_lo(v) + 1e-5f, bf_hi(v) + 1e-5f);
        asm("sqrt.approx.ftz.f32 %0, %1;" : "=f"(c.c0) : "f"(bf_lo(v)));
        asm("sqrt.approx.ftz.f32 %0, %1;" : "=f"(c.c1) : "f"(bf_hi(v)));
      }
      if (S == 3) {
        const uint32_t v = pack_bf16(c.c0, c.c1);
        c.c0 = rcpf(bf_lo(v) * 2.f); c.c1 = rcpf(bf_hi(v) * 2.f);
      }
      pin(c.c0); pin(c.c1);
    }
  } else if constexpr (KIND == K_GATE) {
    constexpr int lo = S < 4 ? S * 3 : 4 + S * 2, hi = S < 4 ? S * 3 + 3 : 6 + S * 2;
    if (S == 0 || c.always) {
#pragma unroll
      for (int i = lo; i < hi; i++) {
        pin(p[2 * i]); pin(p[2 * i + 1]);
        const float k = (i & 1) ? c.c1 : c.c0;
        const float t0 = p[2 * i] * k, t1 = p[2 * i + 1] * k;
        float h0, h1;
        asm("tanh.approx.f32 %0, %1;" : "=f"(h0) : "f"(t0));
        asm("tanh.approx.f32 %0, %1;" : "=f"(h1) : "f"(t1));
        Sv[i] = pack_bf16(fmaf(t0, h0, t0), fmaf(t1, h1, t1));
        pin(Sv[i]);
      }
    }
    if (S >= 1 && n == 8) {
#pragma unroll
      for (int q = 6 * (S - 1); q < 6 * S; q++) lds128(&A[4 * q], c.priv + (q >> 2) * 8192 + (q & 3) * 512);
    }
  } else if constexpr (KIND == K_UP) {
    if (S < 4) {
#pragma unroll
      for (int i = 4 * S; i < 4 * S + 4; i++) {
        pin(p[2 * i]); pin(p[2 * i + 1]);
        Sv[i] = mul_bf16x2(Sv[i], pack_bf16(p[2 * i], p[2 * i + 1]));
      }
      sts128(c.priv + (n & 7) * 8192 + S * 512, &Sv[4 * S]);
    }
    if (S == 3 && n == 8) {
#pragma unroll
      for (int q = 30; q < 36; q++) lds128(&A[4 * q], c.priv + ((q >> 2) & 7) * 8192 + (q & 3) * 512);
    }
  } else {
    if (S == 0) {
      uint32_t v[16];
#pragma unroll
      for (int i = 0; i < 16; i++) {
        pin(p[2 * i]); pin(p[2 * i + 1]);
        v[i] = pack_bf16(p[2 * i], p[2 * i + 1]);
        if ((i & 3) == 0) v[i] = (v[i] & ~1u) | c.tag;
      }
#pragma unroll
      for (int q = 0; q < 4; q++) stg_relaxed(c.dst + q * 32, &v[4 * q]);
    }
    if (S == 2) {
      c.dst = part_ptr(mt, (f + n) & 7, f) + frag_index();
      pinp(c.dst);
      if (n >= 4) ensure_tile(Sv, c.src, c.tag);
#pragma unroll
      for (int i = 0; i < 16; i++) { p[2 * i] = bf_lo(Sv[i]); p[2 * i + 1] = bf_hi(Sv[i]); pin(p[2 * i]); pin(p[2 * i + 1]); }
      c.src = (n < 7 ? part_ptr(mt, (f + n + 2) & 7, f ^ 4) : part_ptr(mt, f, (f + 10 - n) & 7)) + frag_index();
      pinp(c.src);
    }
    if (S == 3 && n >= 3) load_tile(Sv, c.src);
  }
}

template <int KIND, bool ODD, int S>
__device__ __forceinline__ void stage(Ctx& c, uint32_t (&A)[144], float (&d)[32], float (&p)[32], uint32_t (&Sv)[16], int n, int mt, int f) {
  if (!c.ready) mbar_wait(c.sb + bFull + S * 8, ODD);
  const uint32_t dlo = ((c.sb + oW) & 0x3FFFF) >> 4;
  constexpr int o = S * (kSlotBytes >> 4);
  wg_fence();
  wgmma64<S == 0 && KIND != K_XCHG, o>(d, &A[S * 24], dlo);
  wgmma64<false, o + 128>(d, &A[S * 24 + 4], dlo);
  wgmma64<false, o + 256>(d, &A[S * 24 + 8], dlo);
  wgmma64<false, o + 384>(d, &A[S * 24 + 12], dlo);
  wgmma64<false, o + 512>(d, &A[S * 24 + 16], dlo);
  wgmma64<false, o + 640>(d, &A[S * 24 + 20], dlo);
  wg_commit();
  if (KIND != K_FIRST || S > 0) {
    wg_wait<1>();
    if (c.rel) mbar_arrive_cluster(c.relbar + ((S + 5) % 6) * 8);
  }
  c.ready = mbar_probe(c.sb + bFull + ((S + 1) % 6) * 8, S == 5 ? !ODD : ODD);
  epi_slice<KIND, S>(c, A, p, Sv, n, mt, f);
}

template <int KIND, bool ODD>
__device__ __forceinline__ void pass(Ctx& c, uint32_t (&A)[144], float (&d)[32], float (&p)[32], uint32_t (&Sv)[16], int n, int mt, int f) {
  stage<KIND, ODD, 0>(c, A, d, p, Sv, n, mt, f);
  stage<KIND, ODD, 1>(c, A, d, p, Sv, n, mt, f);
  stage<KIND, ODD, 2>(c, A, d, p, Sv, n, mt, f);
  stage<KIND, ODD, 3>(c, A, d, p, Sv, n, mt, f);
  stage<KIND, ODD, 4>(c, A, d, p, Sv, n, mt, f);
  stage<KIND, ODD, 5>(c, A, d, p, Sv, n, mt, f);
}

__global__ void __cluster_dims__(2, 1, 1) __launch_bounds__(384, 1)
ffn_kernel(const __grid_constant__ CUtensorMap tmW1, const __grid_constant__ CUtensorMap tmW3,
           const __grid_constant__ CUtensorMap tmW2, __nv_bfloat16* __restrict__ out, int one) {
  extern __shared__ __align__(1024) unsigned char smem_raw[];
  const uint32_t sb = smem_u32(smem_raw);
  const int rank = blockIdx.x & 1, pr = blockIdx.x >> 1;
  const int q7 = ((pr - 36) * 37) >> 8;
  const int grp = pr < 4 ? 7 : (pr < 36 ? (pr - 4) & 7 : pr - 36 - 7 * q7);
  const int mt = 2 * grp + rank, f = pr < 4 ? 4 + pr : (pr < 36 ? (pr - 4) >> 3 : 4 + q7);
  const int warp = __shfl_sync(0xffffffffu, threadIdx.x >> 5, 0), lane = threadIdx.x & 31;

  if (warp == 10) {
    if (elect_one()) {
#pragma unroll
      for (int i = 0; i < 12; i++) mbar_init(sb + bX + i * 8, 1);
      mbar_init(sb + bTag, 1);
      asm volatile("fence.mbarrier_init.release.cluster;" ::: "memory");
    }
  } else if (warp == 8) {
    if (elect_one()) {
#pragma unroll
      for (int i = 0; i < 6; i++) { mbar_init(sb + bFull + i * 8, 1); mbar_init(sb + bEmpty + i * 8, 4); }
      mbar_init(sb + bP0, 32);
      asm volatile("fence.mbarrier_init.release.cluster;" ::: "memory");
    }
  } else if (warp == 9) {
    if (elect_one()) asm volatile("prefetch.tensormap [%0];" ::"l"(&tmW1) : "memory");
  }
  __syncwarp();
  asm volatile("barrier.cluster.arrive.relaxed.aligned;" ::: "memory");
  auto load_x = [&](int j) {
    const int i = (j & 1) * 6 + (j >> 1);
    mbar_expect(sb + bX + i * 8, 12288);
    bulk_g2s(sb + oR + i * 12288, (const char*)g_hT + (size_t)mt * 147456 + i * 12288, 12288, sb + bX + i * 8);
  };
  if (warp == 10) {
    if (elect_one()) {
      asm volatile("griddepcontrol.wait;" ::: "memory");
#pragma unroll
      for (int j = 0; j < 3; j++) load_x(j);
    }
    __syncwarp();
  }

  if (warp >= 8) {
    asm volatile("setmaxnreg.dec.sync.aligned.u32 24;");
    if (warp == 10) {
      if (elect_one()) {
#pragma unroll
        for (int j = 3; j < 12; j++) load_x(j);
      }
      __syncwarp();
    }
    asm volatile("barrier.cluster.wait.aligned;" ::: "memory");
    if (warp <= 9) {
      if (elect_one()) {
        const int w = warp - 8;
#pragma unroll 1
        for (int p = 0; p < kPasses; p++) {
          const CUtensorMap* tm = p >= 18 ? &tmW2 : ((p & 1) ? &tmW3 : &tmW1);
          const int x = p >= 18 ? (p == 18 ? 8 : ((f + p - 18) & 7)) * 64 : f * 576 + (p >> 1) * 64;
          const int y = (p >= 18 ? f * 576 : 0) + rank * 48 + w * 96;
#pragma unroll
          for (int k = 0; k < 3; k++) {
            const uint32_t bo = (2 * k + w) * 8;
            if (p) mbar_wait(sb + bEmpty + bo, (p - 1) & 1);
            else if (k < 2) mbar_wait(sb + bX + (k ? 5 : 2) * 8, 0);
            mbar_expect(sb + bFull + bo, kSlotBytes);
            tma2d_mc(sb + oW + (2 * k + w) * kSlotBytes + rank * 6144, tm, sb + bFull + bo, x, y + k * 192);
          }
        }
        for (int k = 0; k < 3; k++)
          if (2 * k + w < 5) mbar_wait(sb + bEmpty + (2 * k + w) * 8, 0);
      }
    } else {
      const int w = warp - 10;
      if (w == 0) {
        if (elect_one()) {
          asm volatile("griddepcontrol.wait;" ::: "memory");
          asm volatile("st.shared.u32 [%0], %1;" ::"r"(sb + oTag), "r"(__ldcg(&g_epoch) & 1) : "memory");
          if (blockIdx.x < 2) g_cnt[blockIdx.x * 64] = 0;
        }
        __syncwarp();
        mbar_wait(sb + bX + ((f >> 2) * 6 + 5) * 8, 0);
#pragma unroll 1
        for (int kk = 0; kk < 4; kk++) {
          uint32_t v[4];
          ldsm4t(v, frag_addr(sb, f, lane) + 8 * 8192 + kk * 2048);
          sts128(sb + oH8 + kk * 512 + lane * 16, v);
        }
        mbar_wait(sb + bEmpty, 0);
        asm volatile("fence.proxy.async.shared::cta;" ::: "memory");
        __syncwarp();
        if (elect_one()) {
          mbar_expect(sb + bTag, 16384);
#pragma unroll
          for (int i = 0; i < 2; i++)
            bulk_g2s(sb + oR + i * kRWg + 8 * 8192, (const char*)g_hT + (size_t)mt * 147456 + i * kRWg + f * 8192, 8192, sb + bTag);
        }
        __syncwarp();
      } else {
#pragma unroll 1
        for (int p = kAhead; p < 18; p++) {
          mbar_wait(sb + bFull + 16, (p - kAhead) & 1);
          if (mt < 576 / kBoxRows && elect_one()) {
            tma_prefetch((p & 1) ? &tmW3 : &tmW1, f * 576 + (p >> 1) * 64, mt * kBoxRows);
            if (p >= 9) tma_prefetch(&tmW2, (p == 9 ? 8 : ((f + p - 9) & 7)) * 64, f * 576 + mt * kBoxRows);
          }
        }
      }
      mbar_wait(sb + bP0, 0);
      uint32_t tag;
      asm volatile("ld.shared.u32 %0, [%1];" : "=r"(tag) : "r"(sb + oTag) : "memory");
#pragma unroll 1
      for (int q = 2 * w; q < 2 * w + 2; q++) {
        const uint4* src = part_ptr(mt, 8, 0) + f * 128 + q * 32 + lane;
        float a[8] = {0.f, 0.f, 0.f, 0.f, 0.f, 0.f, 0.f, 0.f};
#pragma unroll 1
        for (int s = 0; s < 8; s += 2) {
          uint32_t v[8];
          ldg_relaxed(v, src);
          ldg_relaxed(v + 4, src + 1024);
          ensure_landed(v, src, tag);
          ensure_landed(v + 4, src + 1024, tag);
#pragma unroll
          for (int i = 0; i < 4; i++) { a[2 * i] += bf_lo(v[i]) + bf_lo(v[4 + i]); a[2 * i + 1] += bf_hi(v[i]) + bf_hi(v[4 + i]); }
          src += 2048;
        }
        {
          uint32_t v[4];
          float k0, k1;
          lds128(v, sb + oH8 + q * 512 + lane * 16);
          asm volatile("ld.shared.v2.f32 {%0, %1}, [%2];" : "=f"(k0), "=f"(k1) : "r"(sb + oK + lane * 8) : "memory");
#pragma unroll
          for (int i = 0; i < 4; i++) {
            a[2 * i] = fmaf(a[2 * i], (i & 1) ? k1 : k0, bf_lo(v[i]));
            a[2 * i + 1] = fmaf(a[2 * i + 1], (i & 1) ? k1 : k0, bf_hi(v[i]));
          }
        }
        uint32_t* o = (uint32_t*)(out + (size_t)(mt * 128 + f * 16 + (lane >> 2)) * kD + 512 + q * 16 + (lane & 3) * 2);
        o[0] = pack_bf16(a[0], a[1]);
        o[4] = pack_bf16(a[4], a[5]);
        o[8 * kD / 2] = pack_bf16(a[2], a[3]);
        o[8 * kD / 2 + 4] = pack_bf16(a[6], a[7]);
      }
    }
  } else {
    asm volatile("setmaxnreg.inc.sync.aligned.u32 240;");
    asm volatile("barrier.cluster.wait.aligned;" ::: "memory");
    const int wg = warp >> 2, tid = threadIdx.x & 127;
    Ctx c;
    c.sb = sb;
    c.rel = (tid & 0x5f) == 0;
    c.relbar = mapa(sb + bEmpty, warp & 1);
    c.priv = sb + oR + wg * kRWg + (warp & 3) * 2048 + lane * 16;
    pin(c.priv);
    c.ready = 0;
    c.always = one != 0;
    uint32_t A[144];
    float acc0[32], acc1[32];
    uint32_t Sv[16];
    {
      const uint32_t base = frag_addr(sb, warp, lane);
      float ss[2][4], qq[4][4];
#pragma unroll
      for (int i = 0; i < 4; i++) ss[0][i] = ss[1][i] = qq[0][i] = qq[1][i] = qq[2][i] = qq[3][i] = 0.f;
      const uint32_t one0 = 0x3f803f80u * one, one1 = (0x3f803f80u - 1) + one;
#pragma unroll
      for (int g = 0; g < 6; g++) {
        mbar_wait(sb + bX + (wg * 6 + g) * 8, 0);
#pragma unroll
        for (int kk = 0; kk < 6; kk++) ldsm4t(&A[g * 24 + kk * 4], base + g * 12288 + kk * 2048);
#pragma unroll
        for (int kk = 0; kk < 6; kk++) {
          const uint32_t* a = &A[g * 24 + kk * 4];
          mma16816(ss[kk & 1], a[0], a[1], a[2], a[3], one0, one1);
        }
#pragma unroll
        for (int kk = 0; kk < 6; kk++) {
          const uint32_t* a = &A[g * 24 + kk * 4];
          mma1688(qq[0], a[0], a[1], a[0]); mma1688(qq[1], a[0], a[1], a[1]);
          mma1688(qq[2], a[2], a[3], a[2]); mma1688(qq[3], a[2], a[3], a[3]);
        }
      }
      const float m0 = (ss[0][0] + ss[1][0]) * (1.f / kD), m1 = (ss[0][2] + ss[1][2]) * (1.f / kD);
      Sv[0] = pack_bf16(m0, m0); Sv[1] = pack_bf16(m1, m1);
      Sv[2] = __float_as_uint(m0); Sv[3] = __float_as_uint(m1);
      centre_group<0>(A, Sv[0], Sv[1]);
      c.c0 = (lane & 4) ? qq[0][1] + qq[2][1] : qq[0][0] + qq[2][0];
      c.c1 = (lane & 4) ? qq[1][3] + qq[3][3] : qq[1][2] + qq[3][2];
      const int src = (lane & 28) | ((lane >> 3) & 3);
      c.c0 = __shfl_sync(0xffffffffu, c.c0, src); c.c1 = __shfl_sync(0xffffffffu, c.c1, src);
      asm volatile("bar.sync 1, 256;" ::: "memory");
    }
    pass<K_FIRST, false>(c, A, acc0, acc1, Sv, 0, mt, f);
#pragma unroll 1
    for (int n = 0; n < 9; n++) {
      pass<K_GATE, true>(c, A, acc1, acc0, Sv, n, mt, f);
      pass<K_UP, false>(c, A, acc0, acc1, Sv, n, mt, f);
    }
    c.c0 *= 2.f; c.c1 *= 2.f;
    if (warp == f) asm volatile("st.shared.v2.f32 [%0], {%1, %2};" ::"r"(sb + oK + lane * 8), "f"(c.c0), "f"(c.c1) : "memory");
#pragma unroll
    for (int i = 0; i < 32; i++) acc1[i] = 0.f;
    mbar_wait(sb + bTag, 0);
    asm volatile("ld.shared.u32 %0, [%1];" : "=r"(c.tag) : "r"(sb + oTag) : "memory");
    c.src = nullptr;
#pragma unroll
    for (int i = 0; i < 16; i++) Sv[i] = 0;
    c.dst = part_ptr(mt, 8, f) + frag_index();
#pragma unroll 1
    for (int n = 1; n < 9; n += 2) {
      pass<K_XCHG, true>(c, A, acc1, acc0, Sv, n, mt, f);
      if (n == 1 && warp == f) mbar_arrive(sb + bP0);
      pass<K_XCHG, false>(c, A, acc0, acc1, Sv, n + 1, mt, f);
    }
    {
      uint32_t last[16];
      const uint4* lsrc = part_ptr(mt, f, (f + 1) & 7) + frag_index();
      load_tile(last, lsrc);
      const uint32_t stg = sb + oR + wg * kRWg + 2 * 8192 + (warp & 3) * 2048;
      uint32_t ra = stg + (lane & 15) * 128 + (((lane >> 4) ^ (lane & 7)) << 4);
      uint32_t rb = stg + (lane >> 3) * 128 + (((lane & 7) ^ (lane >> 3)) << 4);
      __nv_bfloat16* op = out + (size_t)(mt * 128 + warp * 16 + (lane >> 3)) * kD + f * 64 + (lane & 7) * 8;
      pin(ra); pin(rb); pinp(op);
      {
        uint32_t hv[16];
#pragma unroll
        for (int q = 0; q < 4; q++) ldsm4t(&hv[4 * q], frag_addr(sb, warp, lane) + 8 * 8192 + q * 2048);
#pragma unroll
        for (int i = 0; i < 16; i++) {
          const float k = (i & 1) ? c.c1 : c.c0;
          acc1[2 * i] = fmaf(acc1[2 * i], k, bf_lo(hv[i])); acc1[2 * i + 1] = fmaf(acc1[2 * i + 1], k, bf_hi(hv[i]));
          pin(acc1[2 * i]); pin(acc1[2 * i + 1]);
        }
      }
      ensure_tile(Sv, c.src, c.tag);
      {
#pragma unroll
        for (int i = 0; i < 16; i++) {
          const float k = (i & 1) ? c.c1 : c.c0;
          acc1[2 * i] = fmaf(bf_lo(Sv[i]), k, acc1[2 * i]); acc1[2 * i + 1] = fmaf(bf_hi(Sv[i]), k, acc1[2 * i + 1]);
          pin(acc1[2 * i]); pin(acc1[2 * i + 1]);
        }
      }
      wg_wait<0>();
#pragma unroll
      for (int i = 0; i < 32; i++) { pin(acc0[i]); acc1[i] = fmaf(acc0[i], (i & 2) ? c.c1 : c.c0, acc1[i]); pin(acc1[i]); }
      ensure_tile(last, lsrc, c.tag);
#pragma unroll
      for (int j = 0; j < 4; j++) {
        uint32_t v[4];
#pragma unroll
        for (int i = 0; i < 4; i++) {
          const int e = 8 * j + 2 * i;
          const float k = (i & 1) ? c.c1 : c.c0;
          const uint32_t t = last[4 * j + i];
          v[i] = pack_bf16(fmaf(bf_lo(t), k, acc1[e]), fmaf(bf_hi(t), k, acc1[e + 1]));
        }
        stsm4(ra ^ (j << 5), v[0], v[1], v[2], v[3]);
      }
      __syncwarp();
      uint32_t v[16];
#pragma unroll
      for (int i = 0; i < 4; i++) lds128(&v[4 * i], (rb ^ ((i & 1) << 6)) + i * 512);
#pragma unroll
      for (int i = 0; i < 4; i++) stg128(op + i * 4 * kD, &v[4 * i]);
    }
  }
}

constexpr int kSsmThreads = 768;
constexpr uint32_t kUPad = 1024, kUTile = kUPad + 16384;
constexpr uint32_t kKeWords = 16 + 544, kCWords = 96;
constexpr uint32_t kTabCh = 3072;
constexpr uint32_t kFacRow = 272, kFacHalf = 54 * kFacRow;
constexpr uint32_t kQ4Pad = 64, kQ4Words = kQ4Pad + 1568, kQ8Pad = 128, kQ8Words = kQ8Pad + 1024;
constexpr uint32_t kQCh = (kQ4Words + kQ8Words) * 4;
constexpr uint32_t kLnRow = 1168, kLnX = 16 * kLnRow + 64;
constexpr uint32_t aU = 0, aX = aU + 2 * kUTile, aTab = aX + 5 * 4096, aFac = aTab + 5 * kTabCh,
                   aBar = aFac + 10 * kFacHalf + 640, aEnd = aBar + 80;
constexpr uint32_t aQ = aFac, aOut = aQ + 5 * kQCh;
constexpr int kSsmSmem = aEnd;
static_assert(aOut + 12 * 2048 <= aBar, "smem");
static_assert(kLnX <= 2 * kUTile && kLnX <= 5 * 4096, "smem");
static_assert((kKeWords + 2 * kCWords) * 4 <= kTabCh, "smem");
static_assert(aTab % 128 == 0 && aFac % 128 == 0 && kQCh % 128 == 0 && aBar % 8 == 0 && kSsmSmem <= 232448, "smem");

struct Cx { float r, i; };
__device__ __forceinline__ Cx cmul(Cx a, Cx b) { return {fmaf(a.r, b.r, -a.i * b.i), fmaf(a.r, b.i, a.i * b.r)}; }
__device__ __forceinline__ Cx csqr(Cx a) { return {fmaf(a.r, a.r, -a.i * a.i), (a.r + a.r) * a.i}; }
__device__ __forceinline__ Cx cexp_scaled(float lr, float turns, float e) {
  const float t = turns * e, fr = (t - rintf(t)) * 6.283185307179586f, m = ex2f(lr * e);
  return {m * __cosf(fr), m * __sinf(fr)};
}
__device__ __forceinline__ uint32_t ldg32(const void* p) { uint32_t v; asm volatile("ld.volatile.global.u32 %0, [%1];" : "=r"(v) : "l"(p) : "memory"); return v; }
__device__ __forceinline__ uint32_t ldg16(const void* p) { uint32_t v; asm volatile("ld.volatile.global.u16 %0, [%1];" : "=r"(v) : "l"(p) : "memory"); return v; }
__device__ __forceinline__ void sts16(uint32_t a, uint32_t v) { asm volatile("st.shared.u16 [%0], %1;" ::"r"(a), "r"(v) : "memory"); }
__device__ __forceinline__ void sts32(uint32_t a, uint32_t v) { asm volatile("st.shared.u32 [%0], %1;" ::"r"(a), "r"(v) : "memory"); }
__device__ __forceinline__ void sts64(uint32_t a, uint32_t v0, uint32_t v1) { asm volatile("st.shared.v2.u32 [%0], {%1, %2};" ::"r"(a), "r"(v0), "r"(v1) : "memory"); }
__device__ __forceinline__ uint32_t lds32(uint32_t a) { uint32_t v; asm volatile("ld.shared.u32 %0, [%1];" : "=r"(v) : "r"(a) : "memory"); return v; }
__device__ __forceinline__ void ldsm4(uint32_t* r, uint32_t a) {
  asm volatile("ldmatrix.sync.aligned.m8n8.x4.shared.b16 {%0,%1,%2,%3}, [%4];"
               : "=r"(r[0]), "=r"(r[1]), "=r"(r[2]), "=r"(r[3]) : "r"(a) : "memory");
}
__device__ __forceinline__ void stsm4t(uint32_t a, uint32_t r0, uint32_t r1, uint32_t r2, uint32_t r3) {
  asm volatile("stmatrix.sync.aligned.m8n8.x4.trans.shared.b16 [%0], {%1,%2,%3,%4};" ::"r"(a), "r"(r0), "r"(r1), "r"(r2), "r"(r3) : "memory");
}
__device__ __forceinline__ void bar_sync(int id, int n) { asm volatile("bar.sync %0, %1;" ::"r"(id), "r"(n) : "memory"); }
__device__ __forceinline__ void bar_arrive(int id, int n) { asm volatile("bar.arrive %0, %1;" ::"r"(id), "r"(n) : "memory"); }
__device__ __forceinline__ int slot_channel(int b, int s) { return s < 4 ? 4 * b + s : 512 + (b >> 1); }
__device__ __forceinline__ uint32_t u_base(uint32_t sb, int ch) { return sb + aU + (ch >> 9) * kUTile + kUPad + (ch & 3) * 32; }
__device__ __forceinline__ uint32_t u_swz(uint32_t l) { return l ^ ((l >> 3) & 0x70); }

template <bool HI>
__device__ __forceinline__ void conv_unit(uint32_t sb, int slot, int ch, int warp, int lane, uint32_t zero) {
  constexpr int O0 = HI ? 8 : 0;
  const int g = lane >> 2, t = lane & 3;
  const uint32_t tab = sb + aTab + slot * kTabCh;
  float acc[8][4];
#pragma unroll
  for (int o = 0; o < 8; o++) acc[o][0] = acc[o][1] = acc[o][2] = acc[o][3] = 0.f;

  uint32_t ke = tab + (16 + g - 2 * t) * 4;
  uint32_t lin = u_base(sb, ch) + (lane & 7) * 128 + (lane >> 4) * 1024 + ((lane >> 3) & 1) * 16;
  uint32_t am[4];
#pragma unroll
  for (int q = 0; q < 4; q++) am[q] = lds32(ke + (128 * q - 8) * 4);
#pragma unroll 1
  for (int rho = 0; rho < 8; rho++) {
    constexpr int X0 = HI ? 4 : 0, NX = HI ? 12 : 8;
    const uint32_t ga = u_swz(lin);
    uint32_t G[NX][2], a0[4], a1[4], a3[4];
    a0[0] = lds32(ke); a1[0] = lds32(ke + 32);
#pragma unroll
    for (int x = NX - 2; x >= 0; x -= 2) ldsm4(&G[x][0], ga + (X0 + x) * 1024);
#pragma unroll
    for (int q = 1; q < 4; q++) { a0[q] = lds32(ke + 512 * q); a1[q] = lds32(ke + 512 * q + 32); }
#pragma unroll
    for (int q = 0; q < 4; q++) {
      a3[q] = a0[q] ^ zero;
#pragma unroll
      for (int o = 7; o >= 0; o--)
        if (O0 + o - q >= 0) mma16816(acc[o], a0[q], a1[q], am[q], a3[q], G[O0 + o - q - X0][0], G[O0 + o - q - X0][1]);
      am[q] = a1[q] ^ zero;
    }
    ke += 64;
    lin -= 128;
  }

  {
    const uint32_t g0 = u_swz(lin + 1024), g7 = u_swz(lin + 128);
    const uint32_t b0 = lds32(ke + 384 * 4), b1 = lds32(ke + 392 * 4), b3 = b0 ^ zero;
    const uint32_t nk = (lds32(tab + (kKeWords + kCWords + 7) * 4) & 0xffffu) ^ 0x8000u;
    uint32_t F[HI ? 12 : 4][2], E[HI ? 8 : 2][2];
#pragma unroll
    for (int x = (HI ? 10 : 2); x >= 0; x -= 2) ldsm4(&F[x][0], g0 + x * 1024);
#pragma unroll
    for (int x = 0; x < (HI ? 8 : 2); x += 2) ldsm4(&E[x][0], g7 + (x + HI) * 1024);
    const int d = g - 2 * t;
    const uint32_t wp = (d == 4 || d == 5 ? nk : 0u) | (d == 5 || d == 6 ? nk << 16 : 0u);
#pragma unroll
    for (int o = 7; o >= 0; o--)
      if (O0 + o - 4 >= 0) mma16816(acc[o], b0, b1, am[3], b3, F[O0 + o - 4][0], F[O0 + o - 4][1]);
    const uint32_t z0 = zero + zero, z2 = zero * 3, z3 = zero * 5;
    if (HI) {
      const uint32_t wn = (d == -4 || d == -3 ? nk : 0u) | (d == -3 || d == -2 ? nk << 16 : 0u);
      const uint32_t w3 = wn ^ zero, w2 = wp ^ zero, z1 = zero * 7;
#pragma unroll
      for (int o = 7; o >= 0; o--) mma16816(acc[o], wn, z1, w2, w3, F[o][0], F[o][1]);
#pragma unroll
      for (int o = 7; o >= 0; o--) mma16816(acc[o], z0, wp, z2, z3, E[o][0], E[o][1]);
    } else {
      mma16816(acc[7], z0, wp, z2, z3, E[0][0], E[0][1]);
    }
  }

  {
    constexpr int N2 = HI ? 24 : 9, N3 = HI ? 9 : 1, kPd = 2;
    const uint32_t q4 = sb + aQ + slot * kQCh + kQ4Pad * 4, q8 = sb + aQ + slot * kQCh + (kQ4Words + kQ8Pad) * 4;
    uint32_t o4[4], o8[4], B[10][2], a[kPd + 1][4];
#pragma unroll
    for (int i = 0; i < 4; i++) {
      const int w = g - 8 * t + (i & 1) * 8 - (i >> 1) * 32;
      o4[i] = q4 + (w ^ ((w >> 3) & 4)) * 4;
      const int v = g - 16 - 16 * t + (i & 1) * 8 - (i >> 1) * 64;
      o8[i] = q8 + (v ^ (((v >> 5) & 1) * 12)) * 4;
    }
    const uint32_t c4 = tab + (kKeWords + 2 * g + t) * 4, c8 = tab + (kKeWords + kCWords + g + t) * 4;
#pragma unroll
    for (int ks = 0; ks < (HI ? 10 : 9); ks++) { B[ks][0] = lds32(c4 + ks * 32); B[ks][1] = lds32(c4 + ks * 32 + 16); }
    mbar_wait(sb + aBar + 16, 0);
#pragma unroll
    for (int it = -kPd; it < N2 + N3; it++) {
      const int ld = it + kPd;
      if (ld < N2 + N3) {
        const int j = ld < N2 ? ld : ld - N2;
        const int tau = ld < N2 && HI ? ((j & 1) ? 13 + j / 2 : 1 + j / 2) : ((j & 1) ? 8 - j / 2 : j / 2);
#pragma unroll
        for (int i = 0; i < 4; i++) a[ld % (kPd + 1)][i] = ld < N2 ? lds32(o4[i] + tau * 256) : lds32(o8[i] + tau * 512);
      }
      if (it == N2) {
#pragma unroll
        for (int ks = 0; ks < N3; ks++) { B[ks][0] = lds32(c8 + ks * 32); B[ks][1] = lds32(c8 + ks * 32 + 16); }
      }
      if (it >= 0) {
        const int j = it < N2 ? it : it - N2;
        const int tau = it < N2 && HI ? ((j & 1) ? 13 + j / 2 : 1 + j / 2) : ((j & 1) ? 8 - j / 2 : j / 2);
        const uint32_t* av = a[it % (kPd + 1)];
#pragma unroll
        for (int o = 0; o < 8; o++) {
          const int ks = it < N2 ? 2 * (O0 + o) - 6 - tau : O0 + o - 7 - tau;
          if (ks >= 0 && ks < (it < N2 ? 10 : 9)) mma16816(acc[o], av[0], av[1], av[2], av[3], B[ks][0], B[ks][1]);
        }
      }
    }
  }

  const uint32_t ya = sb + aOut + warp * 2048;
  const uint32_t sa = ya + (lane >> 4) * 256 + (lane & 7) * 32 + ((((lane >> 3) ^ (lane >> 2)) & 1) << 4);
  uint4* dst = (uint4*)g_hT + ((size_t)(O0 * 2 + (lane >> 3)) * kD + ch) * 8 + ((lane ^ (lane >> 3 & 1) ^ ch) & 7);
  uint32_t xf[16], y[16];
  mbar_wait(sb + aBar + 8, 0);
#pragma unroll
  for (int i = 0; i < 4; i++) lds128(&xf[4 * i], sb + aX + slot * 4096 + O0 * 256 + i * 512 + lane * 16);
#pragma unroll
  for (int o = 0; o < 8; o += 2)
    stsm4t(sa + o * 256, pack_bf16(acc[o][0], acc[o][1]), pack_bf16(acc[o][2], acc[o][3]),
           pack_bf16(acc[o + 1][0], acc[o + 1][1]), pack_bf16(acc[o + 1][2], acc[o + 1][3]));
  __syncwarp();
#pragma unroll
  for (int i = 0; i < 4; i++) lds128(&y[4 * i], ya + i * 512 + lane * 16);
#pragma unroll
  for (int i = 0; i < 16; i++) y[i] = add_bf16x2(y[i], xf[i]);
#pragma unroll
  for (int i = 0; i < 4; i++) stg128(dst + i * 4 * kD * 8, &y[4 * i]);
  if (!HI && warp == 11) asm volatile("griddepcontrol.launch_dependents;");
}

template <bool BOTH>
__device__ __forceinline__ void box_job(uint32_t sb, int b, int slot, int c) {
  const uint32_t ua = u_base(sb, slot_channel(b, slot));
  const uint32_t ue = ua + (c >> 1) * 128 + (c & 1) * 16, uo = ua + ((c + 1) >> 1) * 128 + (~c & 1) * 16;
  uint32_t v[16];
#pragma unroll
  for (int k = BOTH ? 0 : 1; k < 4; k++) {
    lds128(&v[4 * k], u_swz(((k & 1) ? uo : ue) - (k < 2 ? 128 : 0)));
  }
  constexpr int lo = BOTH ? 5 : 11, hi = BOTH ? 28 : 26;
  float P[29];
  P[lo] = 0.f;
#pragma unroll
  for (int k = lo; k < hi; k++) P[k + 1] = P[k] + ((k & 1) ? bf_hi(v[k >> 1]) : bf_lo(v[k >> 1]));
  const uint32_t odd = (c << 2) & 16;
  uint32_t w[8];
#pragma unroll
  for (int i = 0; i < 8; i++) w[i] = pack_bf16(P[16 + i + 3] - P[16 + i - 2], P[16 + i - 2] - P[16 + i - 5]);
  const uint32_t q4 = (sb + aQ + slot * kQCh + kQ4Pad * 4 + c * 32) ^ odd;
  sts128(q4, w);
  sts128(q4 ^ 16, w + 4);
  if (BOTH) {
#pragma unroll
    for (int i = 0; i < 8; i++) w[i] = pack_bf16(P[16 + i + 5] - P[16 + i - 4], P[16 + i - 4] - P[16 + i - 11]);
    const uint32_t q8 = (q4 + (kQ4Words + kQ8Pad - kQ4Pad) * 4) ^ (odd << 1);
    sts128(q8, w);
    sts128(q8 ^ 16, w + 4);
  }
}

struct SsmArgs {
  const __nv_bfloat16 *x, *ldt, *are, *aim;
  uint32_t zero;
  const __nv_bfloat16 *dsk, *bre, *bim, *cre, *cim;
  const char *w1, *w3;
};

__device__ __forceinline__ void put2(uint32_t a, const Cx& u, const Cx& v) { sts64(a, pack_bf16(u.r, u.i), pack_bf16(v.r, v.i)); }

__device__ __forceinline__ void helper_jobs(uint32_t sb, int b, int warp, int lane) {
  const unsigned long long nh = (b & 1) ? 0x220022311340ull : 0x230023222310ull;
  const unsigned long long nl = 0x110011111111ull;
  const int sh = 4 * (warp - 12);
  const unsigned long long below = (1ull << sh) - 1;
  const unsigned long long hb = nh & below;
  int job = __popcll(hb & 0x111111111111ull) + 2 * __popcll(hb & 0x222222222222ull) + 4 * __popcll(hb & 0x444444444444ull);
  if (warp == 12) {
    const uint32_t zz[4] = {0, 0, 0, 0};
#pragma unroll 1
    for (int s = 0; s < 5; s++) {
      const uint32_t qb = sb + aQ + s * kQCh;
      if (lane < 22) sts128(qb + (lane < 14 ? 16 * lane : (kQ4Pad + 1536) * 4 + 16 * (lane - 14)), zz);
      if (lane < 30) sts128(qb + kQ4Words * 4 + ((16 * lane) ^ ((lane & 8) * 6)), zz);
    }
  }
#pragma unroll 1
  for (int n = (int)((nh >> sh) & 15) + (warp == 12); n > 0; n--, job++)
    box_job<true>(sb, b, warp == 12 ? min(lane, 4) : job >> 2, warp == 12 ? -1 : (job & 3) * 32 + lane);
  const int jl = __popcll(nl & below);
  box_job<false>(sb, b, jl >> 1, 128 + (jl & 1) * 32 + lane);
  __syncwarp();
  if (lane == 0) mbar_arrive(sb + aBar + 16);
}

template <int A, int B>
__device__ __forceinline__ void r_rows(uint32_t fa, Cx (&S)[2][4], const Cx (&zb)[2]) {
#pragma unroll
  for (int j = A; j < B; j++) {
    put2(fa + j * kFacRow, S[0][j & 1], S[1][j & 1]);
#pragma unroll
    for (int m = 0; m < 2; m++)
      if (j < 30) S[m][j & 1] = j == 0 ? zb[m] : cmul(S[m][j & 1], zb[m]);
  }
}
__device__ __forceinline__ void l_rows(uint32_t fl, Cx (&S)[2][4], const Cx (&za)[2], const Cx (&zb)[2]) {
#pragma unroll
  for (int k = 0; k < 11; k++) {
    if (k < 4) {
      put2(fl + 2 * k * kFacRow, S[0][k], S[1][k]);
      put2(fl + (2 * k + 1) * kFacRow, cmul(S[0][k], za[0]), cmul(S[1][k], za[1]));
      S[0][k] = cmul(S[0][k], zb[0]); S[1][k] = cmul(S[1][k], zb[1]);
      put2(fl + (8 + k) * kFacRow, S[0][k], S[1][k]);
      if (k == 3) put2(fl + 21 * kFacRow, cmul(S[0][3], csqr(za[0])), cmul(S[1][3], csqr(za[1])));
    } else {
      S[0][0] = cmul(S[0][0], zb[0]); S[1][0] = cmul(S[1][0], zb[1]);
      put2(fl + (k < 6 ? 4 + 2 * k : 10 + k) * kFacRow, S[0][0], S[1][0]);
      if (k < 6) {
        S[0][2] = cmul(S[0][2], zb[0]); S[1][2] = cmul(S[1][2], zb[1]);
        put2(fl + (5 + 2 * k) * kFacRow, S[0][2], S[1][2]);
      }
    }
  }
}

__global__ void __launch_bounds__(kSsmThreads, 1) ssm_kernel(const SsmArgs a, const __grid_constant__ CUtensorMap tmU,
                                                                const __grid_constant__ CUtensorMap tmX) {
  extern __shared__ __align__(1024) unsigned char smem_raw[];
  const uint32_t sb = smem_u32(smem_raw);
  const int b = blockIdx.x, tid = threadIdx.x;
  uint32_t xv[9];
  if (tid == 0) asm volatile("cp.async.bulk.prefetch.L2.global [%0], 18432;" ::"l"(a.x + (size_t)b * 16 * kD) : "memory");
  if (tid < 512) {
    const uint32_t* xr = (const uint32_t*)a.x + (b * 16 * (kD / 2) + (tid >> 5) * 256 + tid);
#pragma unroll
    for (int i = 0; i < 9; i++) xv[i] = ldg32(xr + i * 32);
  }
  const int warp = __shfl_sync(0xffffffffu, tid >> 5, 0), lane = tid & 31;
  const uint32_t la = sb + (((lane >> 1) & 1) * 8 + 2 * (lane >> 3) + (lane & 1)) * kLnRow + ((lane >> 1) & 1) * 64 + ((lane >> 2) & 1) * 32;
  const uint32_t go = (b * kD + (lane >> 2) + (lane & 2) * 8) * 2 + (lane & 1);

  if (warp < 20) {
    const int slot = warp >> 2, role = (warp + slot) & 3, ch = slot_channel(b, slot);
    const int pi = ch * kN + (role >> 1) * 64 + lane * 2;
    const uint32_t ldt = ldg16(a.ldt + ch), are = ldg32(a.are + pi), aim = ldg32(a.aim + pi);
    uint32_t bre, bim, cre, cim, dsk = 0;
    auto load_bc = [&](uint32_t dep) {
      const int pj = pi + (dep & a.zero);
      if (role & 1) { bre = ldg32(a.bre + pj); bim = ldg32(a.bim + pj); cre = ldg32(a.cre + pj); cim = ldg32(a.cim + pj); }
      else bre = bim = cre = cim = 0;
      if (role == 1) dsk = ldg16(a.dsk + ch);
    };

    if (warp < 16) {
      const uint32_t ra = sb + warp * kLnRow + (warp >> 3) * 64 + lane * 4;
      float s = 0.f, q = 0.f;
      const float x0 = bf_lo(__shfl_sync(0xffffffffu, xv[0], 0));
      load_bc(xv[8]);
#pragma unroll
      for (int i = 0; i < 9; i++) {
        const float lo = bf_lo(xv[i]) - x0, hi = bf_hi(xv[i]) - x0;
        s += lo + hi;
        q = fmaf(lo, lo, fmaf(hi, hi, q));
      }
#pragma unroll
      for (int m = 16; m; m >>= 1) {
        s += __shfl_xor_sync(0xffffffffu, s, m); q += __shfl_xor_sync(0xffffffffu, q, m);
      }
#pragma unroll
      for (int i = 0; i < 9; i++) sts32(ra + aX + i * 128, xv[i]);
      const float dm = s * (1.f / kD), mean = x0 + dm, var = fmaxf(q * (1.f / kD) - dm * dm, 0.f);
      float sd;
      asm("sqrt.approx.f32 %0, %1;" : "=f"(sd) : "f"(round_bf16(round_bf16(var) + 1e-5f)));
      const float r = rcpf(round_bf16(sd));
      const uint32_t mm = pack_bf16(mean, mean);
#pragma unroll
      for (int i = 0; i < 9; i++) {
        const uint32_t d = sub_bf16x2(xv[i], mm);
        sts32(ra + aU + i * 128, pack_bf16(bf_lo(d) * r, bf_hi(d) * r));
      }
    } else {
      load_bc(ldt);
    }
    if (warp < 16) bar_arrive(10, 512 + 32);

    const uint32_t fac = sb + aFac + (slot * 2 + (role >> 1)) * kFacHalf;
    const uint32_t fa = fac + lane * 8 + (role & 1) * 32 * kFacRow;
    Cx za[2], zb[2], S[2][4];
    const float dt = round_bf16(expf(bf_lo(ldt)));
    {
      const float kr = dt * 1.4426950408889634f, ki = dt * ((role & 1) ? -0.15915494309189535f : 0.15915494309189535f);
      const float ea = (role & 1) ? 1.f : 8.f, eb = (role & 1) ? 256.f : 16.f;
#pragma unroll
      for (int m = 0; m < 2; m++) {
        const float lr = (m ? bf_hi(are) : bf_lo(are)) * kr, tn = (m ? bf_hi(aim) : bf_lo(aim)) * ki;
        za[m] = cexp_scaled(lr, tn, ea); zb[m] = cexp_scaled(lr, tn, eb);
      }
    }
    bar_sync(9, 640 + 64);
    {
      uint32_t v[2][4];
      const uint32_t l = la + aU + (warp >> 1) * 64 + (warp & 1) * 16;
      uint4* dst = g_uT + go + ((warp >> 1) * 32 + (warp & 1) * 8) * 2;
      ldsm4t(v[0], l);
      if (warp < 16) ldsm4t(v[1], l + 640);
      stg128(dst, v[0]);
      if (warp < 16) stg128(dst + 320 * 2, v[1]);
    }
    bar_arrive(6, 640 + 32);
    if (role & 1) {
#pragma unroll
      for (int m = 0; m < 2; m++) {
        const Cx z2 = csqr(za[m]), z4 = csqr(z2);
        const Cx c = {m ? bf_hi(cre) : bf_lo(cre), -(m ? bf_hi(cim) : bf_lo(cim))};
        const Cx d = {dt * (m ? bf_hi(bre) : bf_lo(bre)), -dt * (m ? bf_hi(bim) : bf_lo(bim))};
        S[m][0] = cmul(c, d); S[m][1] = cmul(S[m][0], z2); S[m][2] = cmul(S[m][0], z4); S[m][3] = cmul(S[m][1], z4);
      }
      l_rows(fa, S, za, zb);
      bar_arrive(11 + slot, 128);
      bar_sync(1 + slot, 128);
    } else {
#pragma unroll
      for (int m = 0; m < 2; m++) { S[m][0] = {1.f, 0.f}; S[m][1] = za[m]; }
      r_rows<0, 16>(fa, S, zb);
      bar_arrive(1 + slot, 128);
      r_rows<16, 32>(fa, S, zb);
      bar_sync(11 + slot, 128);
    }
    {
      const int mt = ~role & 1;
      const bool up = role >> 1;
      float c[3][4];
#pragma unroll
      for (int n = 0; n < 3; n++) c[n][0] = c[n][1] = c[n][2] = c[n][3] = 0.f;
      const uint32_t aa = fac + (mt * 16 + (lane & 15)) * kFacRow + (lane >> 4) * 16;
      const uint32_t ba = fac + (32 + (lane & 7)) * kFacRow + (lane >> 3) * 16;
#pragma unroll
      for (int k2 = 0; k2 < 4; k2++) {
        uint32_t av[2][4], bv[3][4];
        ldsm4(av[0], aa + k2 * 64); ldsm4(av[1], aa + k2 * 64 + 32);
#pragma unroll
        for (int n = 0; n < 3; n++) ldsm4(bv[n], ba + n * 8 * kFacRow + k2 * 64);
#pragma unroll
        for (int h = 0; h < 2; h++)
#pragma unroll
          for (int n = 0; n < 3; n++) mma16816(c[n], av[h][0], av[h][1], av[h][2], av[h][3], bv[n][2 * h], bv[n][2 * h + 1]);
      }
      const uint32_t ex = fac + mt * 16 * kFacRow + lane * 8;
#pragma unroll
      for (int n = 0; n < 3; n++) sts64(ex + n * 256, __float_as_uint(up ? c[n][0] : c[n][2]), __float_as_uint(up ? c[n][1] : c[n][3]));
      bar_sync((mt ? 11 : 1) + slot, 64);
      float v0[3], v1[3];
#pragma unroll
      for (int n = 0; n < 3; n++) {
        asm volatile("ld.shared.v2.f32 {%0, %1}, [%2];" : "=f"(v0[n]), "=f"(v1[n]) : "r"(ex + (up ? -kFacHalf : kFacHalf) + n * 256) : "memory");
        v0[n] += up ? c[n][2] : c[n][0];
        v1[n] += up ? c[n][3] : c[n][1];
      }
      const int j = mt * 16 + (role >> 1) * 8 + (lane >> 2), t = lane & 3;
      const uint32_t tab = sb + aTab + slot * kTabCh;
      const float k512 = __shfl_down_sync(0xffffffffu, v1[2], 1);
      if (j + t == 0) v0[0] += bf_lo(dsk);
      if (j == 31 && t == 1) v1[1] -= k512;
      const uint32_t w0 = pack_bf16(v1[0], v0[0]), w1 = pack_bf16(v0[1], v1[1]), w2 = pack_bf16(v0[2], v1[2]);
      const uint32_t k0 = tab + (16 + 8 * j + 2 * t) * 4;
      sts16(k0, w0 >> 16); sts32(k0 + 4, w0); sts16(k0 + 10, w0);
      if (t < 2) {
        const uint32_t k1 = tab + (16 + 256 + 8 * j + 4 * t) * 4;
        if (j + t) { sts16(k1 - 4, w1); sts16(k1 + 2, w1); }
        sts16(k1, w1);
        sts32(k1 + 4, __byte_perm(w1, 0, 0x1010));
        sts32(k1 + 8, __byte_perm(w1, 0, 0x1032));
        sts16(k1 + 14, w1 >> 16);
      } else {
        sts32(tab + (kKeWords + 16 + 32 * (t - 2) + j) * 4, w1);
      }
      const uint32_t k2 = tab + (kKeWords + kCWords + 7) * 4 + (64 * t + j) * 2;
      if (t < 2 || (t == 2 && j == 0)) sts16(k2, w2);
      if (t < 2) sts16(k2 + 64, w2 >> 16);
    }
    __syncwarp();
    if (lane == 0) mbar_arrive(sb + aBar + 32 + slot * 8);
  }

  if (warp < 12) {
    bar_arrive(8, kSsmThreads);
    asm volatile("setmaxnreg.inc.sync.aligned.u32 88;");
    const unsigned long long map = (b & 1) ? 0x4fff31092ba8ull : 0x3fff20b91ca8ull;
    const int code = (int)((map >> (4 * warp)) & 15), s = code & 7, c = slot_channel(b, s);
    if (code != 15) {
      mbar_wait(sb + aBar + 32 + s * 8, 0);
      mbar_wait(sb + aBar, 0);
      if (code & 8) conv_unit<true>(sb, s, c, warp, lane, a.zero);
      else conv_unit<false>(sb, s, c, warp, lane, a.zero);
    }
  } else {
    asm volatile("setmaxnreg.dec.sync.aligned.u32 56;");
    const uint32_t z[4] = {0, 0, 0, 0};
    if (warp == 20 || warp == 21) {
      const int k = warp - 20;
      const uint32_t bar = sb + aBar + k * 8, reg = sb + (k ? aX : aU);
      const bool lead = elect_one();
      if (lead) asm volatile("prefetch.tensormap [%0];" ::"l"(k ? &tmX : &tmU) : "memory");
      if (lead && b + k == 0) g_epoch++;
      if (k) {
        bar_arrive(8, kSsmThreads);
        bar_sync(10, 512 + 32);
        bar_sync(7, 64);
#pragma unroll 1
        for (int i = 0; i < 6; i++) {
          uint32_t v[6][4];
#pragma unroll
          for (int j = 0; j < 6; j++) ldsm4t(v[j], la + aX + i * 192 + (j >> 1) * 64 + (j & 1) * 16);
#pragma unroll
          for (int j = 0; j < 6; j++) stg128(g_xT + go + (i * 96 + (j >> 1) * 32 + (j & 1) * 8) * 2, v[j]);
        }
        __syncwarp();
      } else {
        bar_sync(6, 640 + 32);
      }
      if (lead) asm volatile("red.release.gpu.global.add.u32 [%0], 1;" ::"l"(&g_cnt[k * 64]) : "memory");
      if (!k) {
#pragma unroll
        for (int s = 0; s < 4; s++) sts128(reg + (s >> 1) * kUTile + (s & 1) * 512 + lane * 16, z);
        bar_arrive(8, kSsmThreads);
      }
      __syncwarp();
      if (lead) {
        mbar_expect(bar, k ? 5 * 4096 : 2 * 16384);
        asm volatile("fence.proxy.async.shared::cta;" ::: "memory");
        flag_wait(&g_cnt[k * 64], 128);
        asm volatile("fence.proxy.async.global;" ::: "memory");
        if (k) {
#pragma unroll 1
          for (int s = 0; s < 5; s++) tma2d(reg + s * 4096, &tmX, bar, slot_channel(b, s) * 16, 0);
        } else {
          tma2d(reg + kUPad, &tmU, bar, b * 64, 0);
          tma2d(reg + kUTile + kUPad, &tmU, bar, (128 + (b >> 3)) * 64, 0);
        }
      }
      __syncwarp();
      if (!k) {
        bar_arrive(7, 64);
#pragma unroll 1
        for (int p = 0; p < kAhead; p++) {
          const char* wp = ((p & 1) ? a.w3 : a.w1) + (size_t)((b & 15) * 36 + lane) * (kF * 2) + (b >> 4) * 1152 + (p >> 1) * 128;
          asm volatile("prefetch.global.L2 [%0];" ::"l"(wp));
          if (lane < 4) asm volatile("prefetch.global.L2 [%0];" ::"l"(wp + 32 * kF * 2));
        }
      }
    } else {
      if (warp >= 22) {
        if (warp == 22 && elect_one()) {
          mbar_init(sb + aBar, 1); mbar_init(sb + aBar + 8, 1); mbar_init(sb + aBar + 16, 10);
#pragma unroll
          for (int s = 0; s < 5; s++) mbar_init(sb + aBar + 32 + s * 8, 4);
          asm volatile("fence.mbarrier_init.release.cluster;" ::: "memory");
        }
        __syncwarp();
#pragma unroll 1
        for (int i = tid - 704; i < 5 * kTabCh / 16; i += 64) sts128(sb + aTab + i * 16, z);
        bar_arrive(9, 640 + 64);
      }
      bar_sync(8, kSsmThreads);
      mbar_wait(sb + aBar, 0);
      helper_jobs(sb, b, warp, lane);
    }
  }
}

typedef CUresult (*EncodeFn)(CUtensorMap*, CUtensorMapDataType, cuuint32_t, void*, const cuuint64_t*, const cuuint64_t*,
                             const cuuint32_t*, const cuuint32_t*, CUtensorMapInterleave, CUtensorMapSwizzle,
                             CUtensorMapL2promotion, CUtensorMapFloatOOBfill);

void encode2d(EncodeFn fn, CUtensorMap* tm, void* p, int cols, int rows, int bx, int by,
              CUtensorMapL2promotion promo = CU_TENSOR_MAP_L2_PROMOTION_L2_128B) {
  cuuint64_t gd[2] = {(cuuint64_t)cols, (cuuint64_t)rows}, gs[1] = {(cuuint64_t)cols * 2};
  cuuint32_t box[2] = {(cuuint32_t)bx, (cuuint32_t)by}, es[2] = {1, 1};
  fn(tm, CU_TENSOR_MAP_DATA_TYPE_BFLOAT16, 2, p, gd, gs, box, es, CU_TENSOR_MAP_INTERLEAVE_NONE,
     bx == 64 ? CU_TENSOR_MAP_SWIZZLE_128B : CU_TENSOR_MAP_SWIZZLE_32B, promo, CU_TENSOR_MAP_FLOAT_OOB_FILL_NONE);
}

}

extern "C" void kernel_launch(void* const* d_in, const int* in_sizes, int n_in, void* d_out, int out_size) {
  typedef const __nv_bfloat16* P;
  void* fn = nullptr;
  cudaDriverEntryPointQueryResult qr;
  cudaGetDriverEntryPoint("cuTensorMapEncodeTiled", &fn, cudaEnableDefault, &qr);
  void *uT, *xT;
  cudaGetSymbolAddress(&uT, g_uT);
  cudaGetSymbolAddress(&xT, g_xT);
  CUtensorMap t1, t3, t2, tu, tx;
  encode2d((EncodeFn)fn, &tu, uT, kD * 16, 128, 64, 128, CU_TENSOR_MAP_L2_PROMOTION_NONE);
  encode2d((EncodeFn)fn, &tx, xT, kD * 16, 128, 16, 128, CU_TENSOR_MAP_L2_PROMOTION_NONE);
  encode2d((EncodeFn)fn, &t1, d_in[10], kF, kD, 64, kBoxRows);
  encode2d((EncodeFn)fn, &t3, d_in[11], kF, kD, 64, kBoxRows);
  encode2d((EncodeFn)fn, &t2, d_in[12], kD, kF, 64, kBoxRows);
  cudaFuncSetAttribute(ffn_kernel, cudaFuncAttributeMaxDynamicSharedMemorySize, kFfnSmem);

  cudaFuncSetAttribute(ssm_kernel, cudaFuncAttributeMaxDynamicSharedMemorySize, kSsmSmem);
  SsmArgs sa = {(P)d_in[0], (P)d_in[7], (P)d_in[1], (P)d_in[2], 0u, (P)d_in[8], (P)d_in[3], (P)d_in[4], (P)d_in[5], (P)d_in[6],
                (const char*)d_in[10], (const char*)d_in[11]};
  ssm_kernel<<<128, kSsmThreads, kSsmSmem, cudaStreamPerThread>>>(sa, tu, tx);

  cudaLaunchConfig_t cfg = {};
  cfg.gridDim = dim3(128);
  cfg.blockDim = dim3(384);
  cfg.dynamicSmemBytes = kFfnSmem;
  cfg.stream = cudaStreamPerThread;
  cudaLaunchAttribute at[1];
  at[0].id = cudaLaunchAttributeProgrammaticStreamSerialization;
  at[0].val.programmaticStreamSerializationAllowed = 1;
  cfg.attrs = at;
  cfg.numAttrs = 1;
  cudaLaunchKernelEx(&cfg, ffn_kernel, t1, t3, t2, (__nv_bfloat16*)d_out, 1);
}
```

```cpp
#include <cuda_runtime.h>
#include <cuda_bf16.h>
#include <cuda.h>
#include <stdint.h>

namespace {

constexpr int kL = 2048, kD = 576, kF = 4608, kN = 128;
constexpr int kSpinLimit = 100000;

}

__device__ __align__(128) uint4 g_uT[kD * 256];
__device__ __align__(128) uint4 g_xT[kD * 256];
__device__ unsigned g_cnt[2 * 64];
__device__ __align__(1024) __nv_bfloat16 g_hT[kD * kL];
__device__ uint4 g_part[16 * 9 * 8 * 1024];
__device__ unsigned g_epoch;


namespace {

__device__ __forceinline__ uint32_t smem_u32(const void* p) { return (uint32_t)__cvta_generic_to_shared(p); }
__device__ __forceinline__ void mbar_init(uint32_t b, int c) {
  asm volatile("mbarrier.init.shared::cta.b64 [%0], %1;" ::"r"(b), "r"(c));
}
__device__ __forceinline__ void mbar_expect(uint32_t b, int bytes) {
  asm volatile("mbarrier.arrive.expect_tx.shared::cta.b64 _, [%0], %1;" ::"r"(b), "r"(bytes) : "memory");
}
__device__ __forceinline__ void mbar_arrive(uint32_t b) {
  asm volatile("mbarrier.arrive.shared::cta.b64 _, [%0];" ::"r"(b) : "memory");
}
__device__ __forceinline__ void mbar_arrive_cluster(uint32_t b) {
  asm volatile("mbarrier.arrive.shared::cluster.b64 _, [%0];" ::"r"(b) : "memory");
}
__device__ __forceinline__ bool elect_one() {
  uint32_t p;
  asm volatile("{\n.reg .pred q;\nelect.sync _|q, 0xffffffff;\nselp.u32 %0, 1, 0, q;\n}\n" : "=r"(p));
  return p;
}
__device__ __forceinline__ uint32_t mapa(uint32_t a, uint32_t rank) {
  uint32_t r;
  asm volatile("mapa.shared::cluster.u32 %0, %1, %2;" : "=r"(r) : "r"(a), "r"(rank));
  return r;
}
__device__ __forceinline__ void mbar_wait(uint32_t b, uint32_t parity) {
  asm volatile(
      "{\n.reg .pred p;\n.reg .u32 n;\n"
      "mbarrier.try_wait.parity.shared::cta.b64 p, [%0], %1;\n"
      "@p bra DONE;\n"
      "mov.u32 n, 0;\n"
      "LOOP:\n"
      "mbarrier.try_wait.parity.shared::cta.b64 p, [%0], %1;\n"
      "@p bra DONE;\n"
      "add.u32 n, n, 1;\n"
      "setp.lt.u32 p, n, 1000000;\n"
      "@p bra LOOP;\n"
      "trap;\n"
      "DONE:\n}\n" ::"r"(b), "r"(parity) : "memory");
}
__device__ __forceinline__ void flag_wait(const unsigned* p, unsigned target, unsigned backoff) {
  unsigned v;
#pragma unroll 1
  for (int it = 0; it < 10 * kSpinLimit; it++) {
    asm volatile("ld.acquire.gpu.global.u32 %0, [%1];" : "=r"(v) : "l"(p) : "memory");
    if (v >= target) return;
    if (backoff) __nanosleep(backoff);
  }
  asm volatile("trap;");
}
__device__ __forceinline__ void tma2d(uint32_t dst, const CUtensorMap* tm, uint32_t bar, int x, int y) {
  asm volatile("cp.async.bulk.tensor.2d.shared::cluster.global.mbarrier::complete_tx::bytes [%0], [%1, {%3, %4}], [%2];"
               ::"r"(dst), "l"(tm), "r"(bar), "r"(x), "r"(y) : "memory");
}
__device__ __forceinline__ void tma2d_mc(uint32_t dst, const CUtensorMap* tm, uint32_t bar, int x, int y) {
  asm volatile("cp.async.bulk.tensor.2d.shared::cluster.global.mbarrier::complete_tx::bytes.multicast::cluster [%0], [%1, {%3, %4}], [%2], %5;"
               ::"r"(dst), "l"(tm), "r"(bar), "r"(x), "r"(y), "h"((uint16_t)3) : "memory");
}
__device__ __forceinline__ void tma_prefetch(const CUtensorMap* tm, int x, int y) {
  asm volatile("cp.async.bulk.prefetch.tensor.2d.L2.global [%0, {%1, %2}];" ::"l"(tm), "r"(x), "r"(y) : "memory");
}
__device__ __forceinline__ void bulk_g2s(uint32_t dst, const void* src, int bytes, uint32_t bar) {
  asm volatile("cp.async.bulk.shared::cluster.global.mbarrier::complete_tx::bytes [%0], [%1], %2, [%3];"
               ::"r"(dst), "l"(src), "r"(bytes), "r"(bar) : "memory");
}
__device__ __forceinline__ void ldsm4t(uint32_t* r, uint32_t a) {
  asm volatile("ldmatrix.sync.aligned.m8n8.x4.trans.shared.b16 {%0,%1,%2,%3}, [%4];"
               : "=r"(r[0]), "=r"(r[1]), "=r"(r[2]), "=r"(r[3]) : "r"(a) : "memory");
}
__device__ __forceinline__ void stsm4(uint32_t a, uint32_t r0, uint32_t r1, uint32_t r2, uint32_t r3) {
  asm volatile("stmatrix.sync.aligned.m8n8.x4.shared.b16 [%0], {%1,%2,%3,%4};" ::"r"(a), "r"(r0), "r"(r1), "r"(r2), "r"(r3) : "memory");
}
__device__ __forceinline__ void lds128(uint32_t* r, uint32_t a) {
  asm volatile("ld.shared.v4.u32 {%0,%1,%2,%3}, [%4];" : "=r"(r[0]), "=r"(r[1]), "=r"(r[2]), "=r"(r[3]) : "r"(a) : "memory");
}
__device__ __forceinline__ void sts128(uint32_t a, const uint32_t* r) {
  asm volatile("st.shared.v4.u32 [%0], {%1,%2,%3,%4};" ::"r"(a), "r"(r[0]), "r"(r[1]), "r"(r[2]), "r"(r[3]) : "memory");
}
__device__ __forceinline__ void stg128(void* p, const uint32_t* r) {
  asm volatile("st.global.v4.u32 [%0], {%1,%2,%3,%4};" ::"l"(p), "r"(r[0]), "r"(r[1]), "r"(r[2]), "r"(r[3]) : "memory");
}
__device__ __forceinline__ uint32_t pack_bf16(float lo, float hi) {
  uint32_t r;
  asm("cvt.rn.bf16x2.f32 %0, %1, %2;" : "=r"(r) : "f"(hi), "f"(lo));
  return r;
}
__device__ __forceinline__ float bf_lo(uint32_t v) { return __uint_as_float(v << 16); }
__device__ __forceinline__ float bf_hi(uint32_t v) { return __uint_as_float(v & 0xffff0000u); }
__device__ __forceinline__ uint32_t mul_bf16x2(uint32_t a, uint32_t b) {
  uint32_t r;
  asm("mul.rn.bf16x2 %0, %1, %2;" : "=r"(r) : "r"(a), "r"(b));
  return r;
}
__device__ __forceinline__ uint32_t sub_bf16x2(uint32_t a, uint32_t b) {
  uint32_t r;
  asm("sub.rn.bf16x2 %0, %1, %2;" : "=r"(r) : "r"(a), "r"(b));
  return r;
}
__device__ __forceinline__ float ex2f(float x) { float r; asm("ex2.approx.ftz.f32 %0, %1;" : "=f"(r) : "f"(x)); return r; }
__device__ __forceinline__ float rcpf(float x) { float r; asm("rcp.approx.ftz.f32 %0, %1;" : "=f"(r) : "f"(x)); return r; }

#define ACC32(c, d)                                                                                        \
  c(d[0]), c(d[1]), c(d[2]), c(d[3]), c(d[4]), c(d[5]), c(d[6]), c(d[7]), c(d[8]), c(d[9]), c(d[10]),      \
      c(d[11]), c(d[12]), c(d[13]), c(d[14]), c(d[15]), c(d[16]), c(d[17]), c(d[18]), c(d[19]), c(d[20]),  \
      c(d[21]), c(d[22]), c(d[23]), c(d[24]), c(d[25]), c(d[26]), c(d[27]), c(d[28]), c(d[29]), c(d[30]), c(d[31])
#define REGS32                                                                                             \
  "{%0,%1,%2,%3,%4,%5,%6,%7,%8,%9,%10,%11,%12,%13,%14,%15,%16,%17,%18,%19,%20,%21,%22,%23,%24,%25,%26,%27,%28,%29,%30,%31}"

template <bool FIRST, int OFF>
__device__ __forceinline__ void wgmma64(float (&d)[32], const uint32_t* a, uint32_t dlo) {
  if constexpr (FIRST) {
    asm volatile("{\n.reg .pred p;\n.reg .b32 t;\n.reg .b64 db;\nsetp.ne.b32 p, 0, 0;\nadd.u32 t, %36, %37;\nmov.b64 db, {t, 0x40000040};\n"
                 "wgmma.mma_async.sync.aligned.m64n64k16.f32.bf16.bf16 " REGS32 ", {%32,%33,%34,%35}, db, p, 1, 1, 1;\n}\n"
                 : ACC32("=f", d) : "r"(a[0]), "r"(a[1]), "r"(a[2]), "r"(a[3]), "r"(dlo), "n"(OFF));
  } else {
    asm volatile("{\n.reg .pred p;\n.reg .b32 t;\n.reg .b64 db;\nsetp.eq.b32 p, 0, 0;\nadd.u32 t, %36, %37;\nmov.b64 db, {t, 0x40000040};\n"
                 "wgmma.mma_async.sync.aligned.m64n64k16.f32.bf16.bf16 " REGS32 ", {%32,%33,%34,%35}, db, p, 1, 1, 1;\n}\n"
                 : ACC32("+f", d) : "r"(a[0]), "r"(a[1]), "r"(a[2]), "r"(a[3]), "r"(dlo), "n"(OFF));
  }
}
__device__ __forceinline__ void wg_fence() { asm volatile("wgmma.fence.sync.aligned;" ::: "memory"); }
__device__ __forceinline__ void wg_commit() { asm volatile("wgmma.commit_group.sync.aligned;" ::: "memory"); }
template <int N>
__device__ __forceinline__ void wg_wait() { asm volatile("wgmma.wait_group.sync.aligned %0;" ::"n"(N) : "memory"); }
__device__ __forceinline__ void pin(float& v) { asm volatile("" : "+f"(v)::"memory"); }
__device__ __forceinline__ void pin(uint32_t& v) { asm volatile("" : "+r"(v)::"memory"); }

constexpr int kSlotBytes = 12288, kPasses = 27, kBoxRows = 48;
constexpr uint32_t oR = 0, kRWg = 9 * 8192, oW = 2 * kRWg, oBar = oW + 6 * kSlotBytes;
constexpr uint32_t bFull = oBar, bEmpty = bFull + 48, bX = bEmpty + 48, bP0 = bX + 96, bTag = bP0 + 8,
                   oK = bTag + 8, oTag = oK + 256, oH8 = oTag + 16, oEnd = oH8 + 2048;
constexpr int kFfnSmem = oEnd;
static_assert(oH8 % 16 == 0 && kFfnSmem <= 232448, "smem");

__device__ __forceinline__ uint4* part_ptr(int mt, int blk, int slot) { return g_part + ((mt * 9 + blk) * 8 + slot) * 1024; }

struct Ctx {
  uint32_t sb;
  uint32_t relbar;
  bool rel;
  bool always;
  uint32_t priv;
  float c0, c1;
  uint32_t ready;
  uint32_t tag;
  const uint4* src;
  uint4* dst;
};

__device__ __forceinline__ uint32_t mbar_probe(uint32_t b, uint32_t parity) {
  uint32_t ok;
  asm volatile("{\n.reg .pred p;\nmbarrier.test_wait.parity.shared::cta.b64 p, [%1], %2;\nselp.u32 %0, 1, 0, p;\n}\n"
               : "=r"(ok) : "r"(b), "r"(parity) : "memory");
  return ok;
}
__device__ __forceinline__ uint32_t frag_addr(uint32_t sb, int w, int lane) {
  return sb + oR + (w >> 2) * kRWg + ((lane >> 4) * 8 + (lane & 7)) * 128 + (((2 * (w & 3) + ((lane >> 3) & 1)) ^ (lane & 7)) << 4);
}
__device__ __forceinline__ uint32_t frag_index() { return (threadIdx.x >> 5) * 128 + (threadIdx.x & 31); }
__device__ __forceinline__ void ldg_relaxed(uint32_t* v, const uint4* p) {
  asm volatile("{\n.reg .b128 t;\n.reg .b64 lo, hi;\nld.relaxed.gpu.global.b128 t, [%4];\nmov.b128 {lo, hi}, t;\nmov.b64 {%0, %1}, lo;\nmov.b64 {%2, %3}, hi;\n}\n"
               : "=r"(v[0]), "=r"(v[1]), "=r"(v[2]), "=r"(v[3]) : "l"(p) : "memory");
}
__device__ __forceinline__ void stg_relaxed(uint4* p, const uint32_t* v) {
  asm volatile("{\n.reg .b128 t;\n.reg .b64 lo, hi;\nmov.b64 lo, {%1, %2};\nmov.b64 hi, {%3, %4};\nmov.b128 t, {lo, hi};\nst.relaxed.gpu.global.b128 [%0], t;\n}\n"
               ::"l"(p), "r"(v[0]), "r"(v[1]), "r"(v[2]), "r"(v[3]) : "memory");
}
__device__ __forceinline__ uint32_t lane_id() {
  uint32_t v;
  asm volatile("mov.u32 %0, %laneid;" : "=r"(v));
  return v;
}
__device__ __forceinline__ void load_tile(uint32_t (&v)[16], const uint4* p) {
#pragma unroll
  for (int q = 0; q < 4; q++) ldg_relaxed(&v[4 * q], p + q * 32);
}
__device__ __forceinline__ void ensure_tile(uint32_t (&v)[16], const uint4* p, uint32_t tag) {
#pragma unroll 1
  for (int it = 0; it < kSpinLimit; it++) {
    const uint32_t m = (v[0] ^ tag) | (v[4] ^ tag) | (v[8] ^ tag) | (v[12] ^ tag);
    if (!__any_sync(0xffffffffu, m & 1)) break;
    load_tile(v, p);
  }
#pragma unroll
  for (int q = 0; q < 4; q++) v[4 * q] &= ~1u;
}
__device__ __forceinline__ uint32_t add_bf16x2(uint32_t a, uint32_t b) {
  uint32_t r;
  asm("add.rn.bf16x2 %0, %1, %2;" : "=r"(r) : "r"(a), "r"(b));
  return r;
}
template <int G>
__device__ __forceinline__ void centre_group(uint32_t (&A)[144], uint32_t m0, uint32_t m1) {
#pragma unroll
  for (int i = 24 * G; i < 24 * G + 24; i++) { A[i] = sub_bf16x2(A[i], (i & 1) ? m1 : m0); pin(A[i]); }
}
__device__ __forceinline__ void mma16816(float* d, uint32_t a0, uint32_t a1, uint32_t a2, uint32_t a3, uint32_t b0, uint32_t b1) {
  asm volatile("mma.sync.aligned.m16n8k16.row.col.f32.bf16.bf16.f32 {%0,%1,%2,%3}, {%4,%5,%6,%7}, {%8,%9}, {%0,%1,%2,%3};"
               : "+f"(d[0]), "+f"(d[1]), "+f"(d[2]), "+f"(d[3]) : "r"(a0), "r"(a1), "r"(a2), "r"(a3), "r"(b0), "r"(b1));
}
__device__ __forceinline__ void mma1688(float* d, uint32_t a0, uint32_t a1, uint32_t b0) {
  asm volatile("mma.sync.aligned.m16n8k8.row.col.f32.bf16.bf16.f32 {%0,%1,%2,%3}, {%4,%5}, {%6}, {%0,%1,%2,%3};"
               : "+f"(d[0]), "+f"(d[1]), "+f"(d[2]), "+f"(d[3]) : "r"(a0), "r"(a1), "r"(b0));
}
template <typename T>
__device__ __forceinline__ void pinp(T*& v) { asm volatile("" : "+l"(v)::"memory"); }

constexpr int kAhead = 3;

__device__ __forceinline__ int hidden_block(int n) { return n < 8 ? (n + 1) & 7 : 8; }

enum Kind { K_FIRST, K_GATE, K_UP, K_XCHG };

template <int KIND, int S>
__device__ __forceinline__ void epi_slice(Ctx& c, uint32_t (&A)[144], float (&p)[32], uint32_t (&Sv)[16], int n, int mt, int f) {
  if constexpr (KIND == K_FIRST) {
    if (c.always) {
      if constexpr (S < 5) centre_group<S + 1>(A, Sv[0], Sv[1]);
      if (S == 1) {
        const float e0 = __uint_as_float(Sv[2]), e1 = __uint_as_float(Sv[3]);
        uint32_t v = pack_bf16(fmaxf(c.c0 * (1.f / kD) - e0 * e0, 0.f), fmaxf(c.c1 * (1.f / kD) - e1 * e1, 0.f));
        v = pack_bf16(bf_lo(v) + 1e-5f, bf_hi(v) + 1e-5f);
        asm("sqrt.approx.ftz.f32 %0, %1;" : "=f"(c.c0) : "f"(bf_lo(v)));
        asm("sqrt.approx.ftz.f32 %0, %1;" : "=f"(c.c1) : "f"(bf_hi(v)));
      }
      if (S == 3) {
        const uint32_t v = pack_bf16(c.c0, c.c1);
        c.c0 = rcpf(bf_lo(v) * 2.f); c.c1 = rcpf(bf_hi(v) * 2.f);
      }
      pin(c.c0); pin(c.c1);
    }
  } else if constexpr (KIND == K_GATE) {
    constexpr int lo = S ? 3 * S - 3 : 0, hi = S == 5 ? 16 : 3 * S;
    if (S == 1 && n == 8) {
#pragma unroll
      for (int i = 0; i < 16; i++) { A[i] = Sv[i]; pin(A[i]); }
    }
    if (S == 0 || c.always) {
#pragma unroll
      for (int i = lo; i < hi; i++) {
        pin(p[2 * i]); pin(p[2 * i + 1]);
        const float k = (i & 1) ? c.c1 : c.c0;
        const float t0 = p[2 * i] * k, t1 = p[2 * i + 1] * k;
        float h0, h1;
        asm("tanh.approx.f32 %0, %1;" : "=f"(h0) : "f"(t0));
        asm("tanh.approx.f32 %0, %1;" : "=f"(h1) : "f"(t1));
        Sv[i] = pack_bf16(fmaf(t0, h0, t0), fmaf(t1, h1, t1));
        pin(Sv[i]);
      }
    }
    if (S >= 1 && n == 8) {
#pragma unroll
      for (int q = (S == 1 ? 4 : 6 * (S - 1)); q < 6 * S; q++) lds128(&A[4 * q], c.priv + (q >> 2) * 8192 + (q & 3) * 512);
    }
  } else if constexpr (KIND == K_UP) {
    if (S < 4) {
#pragma unroll
      for (int i = 4 * S; i < 4 * S + 4; i++) {
        pin(p[2 * i]); pin(p[2 * i + 1]);
        Sv[i] = mul_bf16x2(Sv[i], pack_bf16(p[2 * i], p[2 * i + 1]));
      }
      if (n < 7) sts128(c.priv + (n + 1) * 8192 + S * 512, &Sv[4 * S]);
      else if (n == 8) {
#pragma unroll
        for (int i = 4 * S; i < 4 * S + 4; i++) { A[128 + i] = Sv[i]; pin(A[128 + i]); }
      }
    }
    if (S == 3 && n == 8) {
#pragma unroll
      for (int q = 30; q < 32; q++) lds128(&A[4 * q], c.priv + (q >> 2) * 8192 + (q & 3) * 512);
    }
  } else {
    if (S == 0) {
      uint32_t v[16];
#pragma unroll
      for (int i = 0; i < 16; i++) {
        pin(p[2 * i]); pin(p[2 * i + 1]);
        v[i] = pack_bf16(p[2 * i], p[2 * i + 1]);
        if ((i & 3) == 0) v[i] = (v[i] & ~1u) | c.tag;
      }
#pragma unroll
      for (int q = 0; q < 4; q++) stg_relaxed(c.dst + q * 32, &v[4 * q]);
    }
    if (S == 2) {
      c.dst = part_ptr(mt, (f + n) & 7, f) + frag_index();
      pinp(c.dst);
      if (n >= 4) ensure_tile(Sv, c.src, c.tag);
#pragma unroll
      for (int i = 0; i < 16; i++) { p[2 * i] = bf_lo(Sv[i]); p[2 * i + 1] = bf_hi(Sv[i]); pin(p[2 * i]); pin(p[2 * i + 1]); }
      c.src = (n < 7 ? part_ptr(mt, (f + n + 2) & 7, f ^ 4) : part_ptr(mt, f, (f + 10 - n) & 7)) + frag_index();
      pinp(c.src);
    }
    if (S == 3 && n >= 3) load_tile(Sv, c.src);
  }
}

template <int KIND, bool ODD, int S>
__device__ __forceinline__ void stage(Ctx& c, uint32_t (&A)[144], float (&d)[32], float (&p)[32], uint32_t (&Sv)[16], int n, int mt, int f) {
  if (!c.ready) mbar_wait(c.sb + bFull + S * 8, ODD);
  const uint32_t dlo = ((c.sb + oW) & 0x3FFFF) >> 4;
  constexpr int o = S * (kSlotBytes >> 4);
  wg_fence();
  wgmma64<S == 0 && KIND != K_XCHG, o>(d, &A[S * 24], dlo);
  wgmma64<false, o + 128>(d, &A[S * 24 + 4], dlo);
  wgmma64<false, o + 256>(d, &A[S * 24 + 8], dlo);
  wgmma64<false, o + 384>(d, &A[S * 24 + 12], dlo);
  wgmma64<false, o + 512>(d, &A[S * 24 + 16], dlo);
  wgmma64<false, o + 640>(d, &A[S * 24 + 20], dlo);
  wg_commit();
  if (KIND != K_FIRST || S > 0) {
    wg_wait<1>();
    if (c.rel) mbar_arrive_cluster(c.relbar + ((S + 5) % 6) * 8);
  }
  c.ready = mbar_probe(c.sb + bFull + ((S + 1) % 6) * 8, S == 5 ? !ODD : ODD);
  epi_slice<KIND, S>(c, A, p, Sv, n, mt, f);
}

template <int KIND, bool ODD>
__device__ __forceinline__ void pass(Ctx& c, uint32_t (&A)[144], float (&d)[32], float (&p)[32], uint32_t (&Sv)[16], int n, int mt, int f) {
  stage<KIND, ODD, 0>(c, A, d, p, Sv, n, mt, f);
  stage<KIND, ODD, 1>(c, A, d, p, Sv, n, mt, f);
  stage<KIND, ODD, 2>(c, A, d, p, Sv, n, mt, f);
  stage<KIND, ODD, 3>(c, A, d, p, Sv, n, mt, f);
  stage<KIND, ODD, 4>(c, A, d, p, Sv, n, mt, f);
  stage<KIND, ODD, 5>(c, A, d, p, Sv, n, mt, f);
}

__global__ void __cluster_dims__(2, 1, 1) __launch_bounds__(384, 1)
ffn_kernel(const char* hT, const __grid_constant__ CUtensorMap tmW1, const __grid_constant__ CUtensorMap tmW3,
           const __grid_constant__ CUtensorMap tmW2, __nv_bfloat16* __restrict__ out, int one) {
  extern __shared__ __align__(1024) unsigned char smem_raw[];
  const uint32_t sb = smem_u32(smem_raw);
  const int rank = blockIdx.x & 1, pr = blockIdx.x >> 1;
  const int q7 = ((pr - 36) * 37) >> 8;
  const int grp = pr < 4 ? 7 : (pr < 36 ? (pr - 4) & 7 : pr - 36 - 7 * q7);
  const int mt = 2 * grp + rank, f = pr < 4 ? 4 + pr : (pr < 36 ? (pr - 4) >> 3 : 4 + q7);
  const int warp = __shfl_sync(0xffffffffu, threadIdx.x >> 5, 0), lane = threadIdx.x & 31;

  if (warp == 10) {
    if (elect_one()) {
#pragma unroll
      for (int i = 0; i < 12; i++) mbar_init(sb + bX + i * 8, 1);
      mbar_init(sb + bTag, 1);
      asm volatile("fence.mbarrier_init.release.cluster;" ::: "memory");
    }
  } else if (warp == 8) {
    if (elect_one()) {
#pragma unroll
      for (int i = 0; i < 6; i++) { mbar_init(sb + bFull + i * 8, 1); mbar_init(sb + bEmpty + i * 8, 4); }
      mbar_init(sb + bP0, 32);
      asm volatile("fence.mbarrier_init.release.cluster;" ::: "memory");
    }
  } else if (warp == 9) {
    if (elect_one()) asm volatile("prefetch.tensormap [%0];" ::"l"(&tmW1) : "memory");
  }
  __syncwarp();
  asm volatile("barrier.cluster.arrive.relaxed.aligned;" ::: "memory");
  auto load_x = [&](int j) {
    const int i = (j & 1) * 6 + (j >> 1);
    mbar_expect(sb + bX + i * 8, 12288);
    bulk_g2s(sb + oR + i * 12288, hT + (size_t)mt * 147456 + i * 12288, 12288, sb + bX + i * 8);
  };
  if (warp == 10) {
    if (elect_one()) {
      asm volatile("griddepcontrol.wait;" ::: "memory");
#pragma unroll
      for (int j = 0; j < 3; j++) load_x(j);
    }
    __syncwarp();
  }

  if (warp >= 8) {
    asm volatile("setmaxnreg.dec.sync.aligned.u32 24;");
    if (warp == 10) {
      if (elect_one()) {
#pragma unroll
        for (int j = 3; j < 12; j++) load_x(j);
      }
      __syncwarp();
    }
    asm volatile("barrier.cluster.wait.aligned;" ::: "memory");
    if (warp <= 9) {
      if (elect_one()) {
        const int w = warp - 8;
#pragma unroll 1
        for (int p = 0; p < kPasses; p++) {
          const CUtensorMap* tm = p >= 18 ? &tmW2 : ((p & 1) ? &tmW3 : &tmW1);
          const int x = p >= 18 ? (p == 18 ? 8 : ((f + p - 18) & 7)) * 64 : f * 576 + hidden_block(p >> 1) * 64;
          const int y = (p >= 18 ? f * 576 : 0) + rank * 48 + w * 96;
#pragma unroll
          for (int k = 0; k < 3; k++) {
            const uint32_t bo = (2 * k + w) * 8;
            if (p) mbar_wait(sb + bEmpty + bo, (p - 1) & 1);
            else if (k < 2) mbar_wait(sb + bX + (k ? 5 : 2) * 8, 0);
            mbar_expect(sb + bFull + bo, kSlotBytes);
            tma2d_mc(sb + oW + (2 * k + w) * kSlotBytes + rank * 6144, tm, sb + bFull + bo, x, y + k * 192);
          }
        }
        for (int k = 0; k < 3; k++)
          if (2 * k + w < 5) mbar_wait(sb + bEmpty + (2 * k + w) * 8, 0);
      }
    } else {
      const int w = warp - 10;
      if (w == 0) {
        if (elect_one()) {
          asm volatile("griddepcontrol.wait;" ::: "memory");
          asm volatile("st.shared.u32 [%0], %1;" ::"r"(sb + oTag), "r"(__ldcg(&g_epoch) & 1) : "memory");
          if (blockIdx.x < 2) g_cnt[blockIdx.x * 64] = 0;
        }
        __syncwarp();
        mbar_wait(sb + bX + ((f >> 2) * 6 + 5) * 8, 0);
#pragma unroll 1
        for (int kk = 0; kk < 4; kk++) {
          uint32_t v[4];
          ldsm4t(v, frag_addr(sb, f, lane) + 8 * 8192 + kk * 2048);
          sts128(sb + oH8 + kk * 512 + lane * 16, v);
        }
        mbar_wait(sb + bEmpty, 0);
        asm volatile("fence.proxy.async.shared::cta;" ::: "memory");
        __syncwarp();
        if (elect_one()) {
          mbar_expect(sb + bTag, 16384);
#pragma unroll
          for (int i = 0; i < 2; i++)
            bulk_g2s(sb + oR + i * kRWg + 8 * 8192, hT + (size_t)mt * 147456 + i * kRWg + f * 8192, 8192, sb + bTag);
        }
        __syncwarp();
      } else {
#pragma unroll 1
        for (int p = kAhead; p < 18; p++) {
          mbar_wait(sb + bFull + 16, (p - kAhead) & 1);
          if (mt < 576 / kBoxRows && elect_one()) {
            tma_prefetch((p & 1) ? &tmW3 : &tmW1, f * 576 + hidden_block(p >> 1) * 64, mt * kBoxRows);
            if (p >= 9) tma_prefetch(&tmW2, (p == 9 ? 8 : ((f + p - 9) & 7)) * 64, f * 576 + mt * kBoxRows);
          }
        }
      }
      mbar_wait(sb + bP0, 0);
      uint32_t tag;
      asm volatile("ld.shared.u32 %0, [%1];" : "=r"(tag) : "r"(sb + oTag) : "memory");
#pragma unroll 1
      for (int q = 2 * w; q < 2 * w + 2; q++) {
        const uint4* src = part_ptr(mt, 8, 0) + (f * 128 + q * 32 + lane_id());
        float a[8] = {0.f, 0.f, 0.f, 0.f, 0.f, 0.f, 0.f, 0.f};
#pragma unroll 1
        for (int it = 0; (it & 7) < 4; it += 8) {
          uint32_t v[8];
          ldg_relaxed(v, src);
          ldg_relaxed(v + 4, src + 1024);
          if (__any_sync(0xffffffffu, ((v[0] ^ tag) | (v[4] ^ tag)) & 1) && it < 8 * kSpinLimit) continue;
          v[0] &= ~1u; v[4] &= ~1u;
#pragma unroll
          for (int i = 0; i < 4; i++) { a[2 * i] = a[2 * i] + bf_lo(v[i]) + bf_lo(v[4 + i]); a[2 * i + 1] = a[2 * i + 1] + bf_hi(v[i]) + bf_hi(v[4 + i]); }
          src += 2048;
          it++;
        }
        const uint32_t l = lane_id();
        uint32_t v[4];
        float k0, k1;
        lds128(v, sb + oH8 + q * 512 + l * 16);
        asm volatile("ld.shared.v2.f32 {%0, %1}, [%2];" : "=f"(k0), "=f"(k1) : "r"(sb + oK + l * 8) : "memory");
#pragma unroll
        for (int i = 0; i < 4; i++)
          v[i] = pack_bf16(fmaf(a[2 * i], (i & 1) ? k1 : k0, bf_lo(v[i])), fmaf(a[2 * i + 1], (i & 1) ? k1 : k0, bf_hi(v[i])));
        uint32_t* o = (uint32_t*)out + ((mt * 128 + f * 16 + (l >> 2)) * (kD / 2) + 256 + q * 8 + (l & 3));
        o[0] = v[0];
        o[4] = v[2];
        o[8 * kD / 2] = v[1];
        o[8 * kD / 2 + 4] = v[3];
      }
    }
  } else {
    asm volatile("setmaxnreg.inc.sync.aligned.u32 240;");
    asm volatile("barrier.cluster.wait.aligned;" ::: "memory");
    const int wg = warp >> 2, tid = threadIdx.x & 127;
    Ctx c;
    c.sb = sb;
    c.rel = (tid & 0x5f) == 0;
    c.relbar = mapa(sb + bEmpty, warp & 1);
    c.priv = sb + oR + wg * kRWg + (warp & 3) * 2048 + lane * 16;
    pin(c.priv);
    c.ready = 0;
    c.always = one != 0;
    uint32_t A[144];
    float acc0[32], acc1[32];
    uint32_t Sv[16];
    {
      const uint32_t base = frag_addr(sb, warp, lane);
      float ss[2][4], qq[4][4];
#pragma unroll
      for (int i = 0; i < 4; i++) ss[0][i] = ss[1][i] = qq[0][i] = qq[1][i] = qq[2][i] = qq[3][i] = 0.f;
      const uint32_t one0 = 0x3f803f80u * one, one1 = (0x3f803f80u - 1) + one;
#pragma unroll
      for (int g = 0; g < 6; g++) {
        mbar_wait(sb + bX + (wg * 6 + g) * 8, 0);
#pragma unroll
        for (int kk = 0; kk < 6; kk++) ldsm4t(&A[g * 24 + kk * 4], base + g * 12288 + kk * 2048);
#pragma unroll
        for (int kk = 0; kk < 6; kk++) {
          const uint32_t* a = &A[g * 24 + kk * 4];
          mma16816(ss[kk & 1], a[0], a[1], a[2], a[3], one0, one1);
        }
#pragma unroll
        for (int kk = 0; kk < 6; kk++) {
          const uint32_t* a = &A[g * 24 + kk * 4];
          mma1688(qq[0], a[0], a[1], a[0]); mma1688(qq[1], a[0], a[1], a[1]);
          mma1688(qq[2], a[2], a[3], a[2]); mma1688(qq[3], a[2], a[3], a[3]);
        }
      }
      const float m0 = (ss[0][0] + ss[1][0]) * (1.f / kD), m1 = (ss[0][2] + ss[1][2]) * (1.f / kD);
      Sv[0] = pack_bf16(m0, m0); Sv[1] = pack_bf16(m1, m1);
      Sv[2] = __float_as_uint(m0); Sv[3] = __float_as_uint(m1);
      centre_group<0>(A, Sv[0], Sv[1]);
      c.c0 = (lane & 4) ? qq[0][1] + qq[2][1] : qq[0][0] + qq[2][0];
      c.c1 = (lane & 4) ? qq[1][3] + qq[3][3] : qq[1][2] + qq[3][2];
      const int src = (lane & 28) | ((lane >> 3) & 3);
      c.c0 = __shfl_sync(0xffffffffu, c.c0, src); c.c1 = __shfl_sync(0xffffffffu, c.c1, src);
      asm volatile("bar.sync 1, 256;" ::: "memory");
    }
    pass<K_FIRST, false>(c, A, acc0, acc1, Sv, 0, mt, f);
#pragma unroll 1
    for (int n = 0; n < 9; n++) {
      pass<K_GATE, true>(c, A, acc1, acc0, Sv, n, mt, f);
      pass<K_UP, false>(c, A, acc0, acc1, Sv, n, mt, f);
    }
    c.c0 *= 2.f; c.c1 *= 2.f;
    if (warp == f) asm volatile("st.shared.v2.f32 [%0], {%1, %2};" ::"r"(sb + oK + lane * 8), "f"(c.c0), "f"(c.c1) : "memory");
#pragma unroll
    for (int i = 0; i < 32; i++) acc1[i] = 0.f;
    mbar_wait(sb + bTag, 0);
    asm volatile("ld.shared.u32 %0, [%1];" : "=r"(c.tag) : "r"(sb + oTag) : "memory");
    c.src = nullptr;
#pragma unroll
    for (int i = 0; i < 16; i++) Sv[i] = 0;
    c.dst = part_ptr(mt, 8, f) + frag_index();
#pragma unroll 1
    for (int n = 1; n < 9; n += 2) {
      pass<K_XCHG, true>(c, A, acc1, acc0, Sv, n, mt, f);
      if (n == 1 && warp == f) mbar_arrive(sb + bP0);
      pass<K_XCHG, false>(c, A, acc0, acc1, Sv, n + 1, mt, f);
    }
    {
      uint32_t last[16];
      const uint4* lsrc = part_ptr(mt, f, (f + 1) & 7) + frag_index();
      load_tile(last, lsrc);
      const uint32_t stg = sb + oR + wg * kRWg + 2 * 8192 + (warp & 3) * 2048;
      uint32_t ra = stg + (lane & 15) * 128 + (((lane >> 4) ^ (lane & 7)) << 4);
      uint32_t rb = stg + (lane >> 3) * 128 + (((lane & 7) ^ (lane >> 3)) << 4);
      __nv_bfloat16* op = out + (size_t)(mt * 128 + warp * 16 + (lane >> 3)) * kD + f * 64 + (lane & 7) * 8;
      pin(ra); pin(rb); pinp(op);
      {
        uint32_t hv[16];
#pragma unroll
        for (int q = 0; q < 4; q++) ldsm4t(&hv[4 * q], frag_addr(sb, warp, lane) + 8 * 8192 + q * 2048);
#pragma unroll
        for (int i = 0; i < 16; i++) {
          const float k = (i & 1) ? c.c1 : c.c0;
          acc1[2 * i] = fmaf(acc1[2 * i], k, bf_lo(hv[i])); acc1[2 * i + 1] = fmaf(acc1[2 * i + 1], k, bf_hi(hv[i]));
          pin(acc1[2 * i]); pin(acc1[2 * i + 1]);
        }
      }
      ensure_tile(Sv, c.src, c.tag);
      wg_wait<0>();
#pragma unroll
      for (int i = 0; i < 32; i++) { pin(acc0[i]); acc1[i] = fmaf(acc0[i], (i & 2) ? c.c1 : c.c0, acc1[i]); pin(acc1[i]); }
      ensure_tile(last, lsrc, c.tag);
#pragma unroll
      for (int j = 0; j < 4; j++) {
        uint32_t v[4];
#pragma unroll
        for (int i = 0; i < 4; i++) {
          const int e = 8 * j + 2 * i;
          const float k = (i & 1) ? c.c1 : c.c0;
          const uint32_t t = add_bf16x2(last[4 * j + i], Sv[4 * j + i]);
          v[i] = pack_bf16(fmaf(bf_lo(t), k, acc1[e]), fmaf(bf_hi(t), k, acc1[e + 1]));
        }
        stsm4(ra ^ (j << 5), v[0], v[1], v[2], v[3]);
      }
      __syncwarp();
      uint32_t v[16];
#pragma unroll
      for (int i = 0; i < 4; i++) lds128(&v[4 * i], (rb ^ ((i & 1) << 6)) + i * 512);
#pragma unroll
      for (int i = 0; i < 4; i++) stg128(op + i * 4 * kD, &v[4 * i]);
    }
  }
}

constexpr int kSsmThreads = 768;
constexpr uint32_t kUPad = 1024, kUTile = kUPad + 16384;
constexpr uint32_t kKeWords = 16 + 544, kCWords = 96;
constexpr uint32_t kTabCh = 3072;
constexpr uint32_t kFacRow = 272, kFacHalf = 54 * kFacRow;
constexpr uint32_t kQ4Pad = 64, kQ4Words = kQ4Pad + 1568, kQ8Pad = 128, kQ8Words = kQ8Pad + 1024;
constexpr uint32_t kQCh = (kQ4Words + kQ8Words) * 4;
constexpr uint32_t kLnRow = 1168, kLnX = 16 * kLnRow + 64;
constexpr uint32_t aU = 0, aX = aU + 2 * kUTile, aTab = aX + 5 * 4096, aFac = aTab + 5 * kTabCh,
                   aBar = aFac + 10 * kFacHalf + 640, aEnd = aBar + 80;
constexpr uint32_t aQ = aFac, aOut = aQ + 5 * kQCh;
constexpr int kSsmSmem = aEnd;
static_assert(aOut + 12 * 2048 <= aBar, "smem");
static_assert(kLnX <= 2 * kUTile && kLnX <= 5 * 4096, "smem");
static_assert((kKeWords + 2 * kCWords) * 4 <= kTabCh, "smem");
static_assert(aTab % 128 == 0 && aFac % 128 == 0 && kQCh % 128 == 0 && aBar % 8 == 0 && kSsmSmem <= 232448, "smem");

struct Cx { float r, i; };
__device__ __forceinline__ Cx cmul(Cx a, Cx b) { return {fmaf(a.r, b.r, -a.i * b.i), fmaf(a.r, b.i, a.i * b.r)}; }
__device__ __forceinline__ Cx csqr(Cx a) { return {fmaf(a.r, a.r, -a.i * a.i), (a.r + a.r) * a.i}; }
__device__ __forceinline__ Cx cexp2(float lr, float turns) {
  const float fr = (turns - ((turns + 12582912.f) - 12582912.f)) * 6.283185307179586f, m = ex2f(lr);
  return {m * __cosf(fr), m * __sinf(fr)};
}
__device__ __forceinline__ uint32_t ldg32(const void* p) { uint32_t v; asm volatile("ld.volatile.global.u32 %0, [%1];" : "=r"(v) : "l"(p) : "memory"); return v; }
__device__ __forceinline__ uint32_t ldg16(const void* p) { uint32_t v; asm volatile("ld.volatile.global.u16 %0, [%1];" : "=r"(v) : "l"(p) : "memory"); return v; }
__device__ __forceinline__ void sts16(uint32_t a, uint32_t v) { asm volatile("st.shared.u16 [%0], %1;" ::"r"(a), "r"(v) : "memory"); }
__device__ __forceinline__ void sts32(uint32_t a, uint32_t v) { asm volatile("st.shared.u32 [%0], %1;" ::"r"(a), "r"(v) : "memory"); }
__device__ __forceinline__ void sts64(uint32_t a, uint32_t v0, uint32_t v1) { asm volatile("st.shared.v2.u32 [%0], {%1, %2};" ::"r"(a), "r"(v0), "r"(v1) : "memory"); }
__device__ __forceinline__ uint32_t lds32(uint32_t a) { uint32_t v; asm volatile("ld.shared.u32 %0, [%1];" : "=r"(v) : "r"(a) : "memory"); return v; }
__device__ __forceinline__ void lds64(uint32_t* r, uint32_t a) { asm volatile("ld.shared.v2.u32 {%0, %1}, [%2];" : "=r"(r[0]), "=r"(r[1]) : "r"(a) : "memory"); }
__device__ __forceinline__ int q_word(int m, int g) { return (16 * m + 2 * g) ^ ((m & 2) << 2); }
__device__ __forceinline__ void ldsm4(uint32_t* r, uint32_t a) {
  asm volatile("ldmatrix.sync.aligned.m8n8.x4.shared.b16 {%0,%1,%2,%3}, [%4];"
               : "=r"(r[0]), "=r"(r[1]), "=r"(r[2]), "=r"(r[3]) : "r"(a) : "memory");
}
__device__ __forceinline__ void stsm4t(uint32_t a, uint32_t r0, uint32_t r1, uint32_t r2, uint32_t r3) {
  asm volatile("stmatrix.sync.aligned.m8n8.x4.trans.shared.b16 [%0], {%1,%2,%3,%4};" ::"r"(a), "r"(r0), "r"(r1), "r"(r2), "r"(r3) : "memory");
}
__device__ __forceinline__ void bar_sync(int id, int n) { asm volatile("bar.sync %0, %1;" ::"r"(id), "r"(n) : "memory"); }
__device__ __forceinline__ void bar_arrive(int id, int n) { asm volatile("bar.arrive %0, %1;" ::"r"(id), "r"(n) : "memory"); }
__device__ __forceinline__ int slot_channel(int b, int s) { return s < 4 ? 4 * b + s : 512 + (b >> 1); }
__device__ __forceinline__ uint32_t u_base(uint32_t sb, int ch) { return sb + aU + (ch >> 9) * kUTile + kUPad + (ch & 3) * 32; }
__device__ __forceinline__ uint32_t u_swz(uint32_t l) { return l ^ ((l >> 3) & 0x70); }

template <bool HI>
__device__ __forceinline__ void conv_unit(uint32_t sb, int slot, int ch, int warp, int lane, uint32_t zero) {
  constexpr int O0 = HI ? 8 : 0;
  const int g = lane >> 2, t = lane & 3;
  const uint32_t tab = sb + aTab + slot * kTabCh;
  float acc[8][4];
#pragma unroll
  for (int o = 0; o < 8; o++) acc[o][0] = acc[o][1] = acc[o][2] = acc[o][3] = 0.f;

  uint32_t ke = tab + (16 + g - 2 * t) * 4;
  uint32_t lin = u_base(sb, ch) + (lane & 7) * 128 + (lane >> 4) * 1024 + ((lane >> 3) & 1) * 16;
  uint32_t am[4];
#pragma unroll
  for (int q = 0; q < 4; q++) am[q] = lds32(ke + (128 * q - 8) * 4);
#pragma unroll 2
  for (int rho = 0; rho < 8; rho++) {
    constexpr int X0 = HI ? 4 : 0, NX = HI ? 12 : 8;
    const uint32_t ga = u_swz(lin);
    uint32_t G[NX][2], a0[4], a1[4], a3[4];
    a0[0] = lds32(ke); a1[0] = lds32(ke + 32);
#pragma unroll
    for (int x = NX - 2; x >= 0; x -= 2) ldsm4(&G[x][0], ga + (X0 + x) * 1024);
#pragma unroll
    for (int q = 1; q < 4; q++) { a0[q] = lds32(ke + 512 * q); a1[q] = lds32(ke + 512 * q + 32); }
#pragma unroll
    for (int q = 0; q < 4; q++) {
      a3[q] = a0[q] ^ zero;
#pragma unroll
      for (int o = 7; o >= 0; o--)
        if (O0 + o - q >= 0) mma16816(acc[o], a0[q], a1[q], am[q], a3[q], G[O0 + o - q - X0][0], G[O0 + o - q - X0][1]);
      am[q] = a1[q] ^ zero;
    }
    ke += 64;
    lin -= 128;
  }

  {
    const uint32_t g0 = u_swz(lin + 1024), g7 = u_swz(lin + 128);
    const uint32_t b0 = lds32(ke + 384 * 4), b1 = lds32(ke + 392 * 4), b3 = b0 ^ zero;
    const uint32_t nk = (lds32(tab + (kKeWords + kCWords + 7) * 4) & 0xffffu) ^ 0x8000u;
    uint32_t F[HI ? 12 : 4][2], E[HI ? 8 : 2][2];
#pragma unroll
    for (int x = (HI ? 10 : 2); x >= 0; x -= 2) ldsm4(&F[x][0], g0 + x * 1024);
#pragma unroll
    for (int x = 0; x < (HI ? 8 : 2); x += 2) ldsm4(&E[x][0], g7 + (x + HI) * 1024);
    const int d = g - 2 * t;
    const uint32_t wp = (d == 4 || d == 5 ? nk : 0u) | (d == 5 || d == 6 ? nk << 16 : 0u);
#pragma unroll
    for (int o = 7; o >= 0; o--)
      if (O0 + o - 4 >= 0) mma16816(acc[o], b0, b1, am[3], b3, F[O0 + o - 4][0], F[O0 + o - 4][1]);
    const uint32_t z0 = zero + zero, z2 = zero * 3, z3 = zero * 5;
    if (HI) {
      const uint32_t wn = (d == -4 || d == -3 ? nk : 0u) | (d == -3 || d == -2 ? nk << 16 : 0u);
      const uint32_t w3 = wn ^ zero, w2 = wp ^ zero, z1 = zero * 7;
#pragma unroll
      for (int o = 7; o >= 0; o--) mma16816(acc[o], wn, z1, w2, w3, F[o][0], F[o][1]);
#pragma unroll
      for (int o = 7; o >= 0; o--) mma16816(acc[o], z0, wp, z2, z3, E[o][0], E[o][1]);
    } else {
      mma16816(acc[7], z0, wp, z2, z3, E[0][0], E[0][1]);
    }
  }

  {
    constexpr int N2 = HI ? 24 : 9, N3 = HI ? 9 : 1, kPd = 4;
    const uint32_t q4 = sb + aQ + slot * kQCh + kQ4Pad * 4, q8 = sb + aQ + slot * kQCh + (kQ4Words + kQ8Pad) * 4;
    uint32_t B[10][2], a[kPd + 1][4];
    const uint32_t o40 = q4 + q_word(-t, g) * 4, o41 = q4 + q_word(-t - 1, g) * 4 + 4, o8 = q8 + q_word(-t - 1, g) * 4;
    const uint32_t c4 = tab + (kKeWords + 2 * g + 2 * t) * 4, c8 = tab + (kKeWords + kCWords + g + t) * 4;
#pragma unroll
    for (int ks = 0; ks < (HI ? 10 : 9); ks++) lds64(B[ks], c4 + ks * 32);
    mbar_wait(sb + aBar + 16, 0);
#pragma unroll
    for (int it = -kPd; it < N2 + N3; it++) {
      const int ld = it + kPd;
      if (ld < N2 + N3) {
        const int j = ld < N2 ? ld : ld - N2;
        const int tau = ld < N2 && HI ? ((j & 1) ? 13 + j / 2 : 1 + j / 2) : ((j & 1) ? 8 - j / 2 : j / 2);
        uint32_t* av = a[ld % (kPd + 1)];
        if (ld < N2) {
          lds64(av, o40 + tau * 256);
          av[2] = lds32(o41 + tau * 256);
          av[3] = av[0] ^ zero;
        } else {
          lds64(av, o8 + tau * 512);
          lds64(av + 2, o8 + tau * 512 - 256);
        }
      }
      if (HI && it == 29) asm volatile("griddepcontrol.launch_dependents;");
      if (it == N2) {
#pragma unroll
        for (int ks = 0; ks < N3; ks++) { B[ks][0] = lds32(c8 + ks * 32); B[ks][1] = lds32(c8 + ks * 32 + 16); }
      }
      if (it >= 0) {
        const int j = it < N2 ? it : it - N2;
        const int tau = it < N2 && HI ? ((j & 1) ? 13 + j / 2 : 1 + j / 2) : ((j & 1) ? 8 - j / 2 : j / 2);
        const uint32_t* av = a[it % (kPd + 1)];
#pragma unroll
        for (int o = 0; o < 8; o++) {
          const int ks = it < N2 ? 2 * (O0 + o) - 6 - tau : O0 + o - 7 - tau;
          if (ks >= 0 && ks < (it < N2 ? 10 : 9)) mma16816(acc[o], av[0], av[1], av[2], av[3], B[ks][0], B[ks][1]);
        }
      }
    }
  }

  const uint32_t ya = sb + aOut + warp * 2048;
  const uint32_t sa = ya + (lane >> 4) * 256 + (lane & 7) * 32 + ((((lane >> 3) ^ (lane >> 2)) & 1) << 4);
  uint4* dst = (uint4*)g_hT + ((size_t)(O0 * 2 + (lane >> 3)) * kD + ch) * 8 + ((lane ^ (lane >> 3 & 1) ^ ch) & 7);
  uint32_t xf[16], y[16];
  mbar_wait(sb + aBar + 8, 0);
#pragma unroll
  for (int i = 0; i < 4; i++) lds128(&xf[4 * i], sb + aX + slot * 4096 + O0 * 256 + i * 512 + lane * 16);
#pragma unroll
  for (int o = 0; o < 8; o += 2)
    stsm4t(sa + o * 256, pack_bf16(acc[o][0], acc[o][1]), pack_bf16(acc[o][2], acc[o][3]),
           pack_bf16(acc[o + 1][0], acc[o + 1][1]), pack_bf16(acc[o + 1][2], acc[o + 1][3]));
  __syncwarp();
#pragma unroll
  for (int i = 0; i < 4; i++) lds128(&y[4 * i], ya + i * 512 + lane * 16);
#pragma unroll
  for (int i = 0; i < 16; i++) y[i] = add_bf16x2(y[i], xf[i]);
#pragma unroll
  for (int i = 0; i < 4; i++) stg128(dst + i * 4 * kD * 8, &y[4 * i]);
}

template <bool BOTH>
__device__ __forceinline__ void box_job(uint32_t sb, int b, int slot, int blk) {
  const uint32_t ua = u_base(sb, slot_channel(b, slot)) + blk * 128;
  uint32_t v[20];
  const uint32_t u0 = u_swz(ua - 128), u1 = u_swz(ua);
  if (BOTH) lds128(&v[0], u0);
  lds128(&v[4], u0 ^ 16);
  lds128(&v[8], u1);
  lds128(&v[12], u1 ^ 16);
  lds128(&v[16], u_swz(ua + 128));
  constexpr int lo = BOTH ? 5 : 11, hi = BOTH ? 36 : 34;
  float P[37];
  P[lo] = 0.f;
#pragma unroll
  for (int k = lo; k < hi; k++) P[k + 1] = P[k] + ((k & 1) ? bf_hi(v[k >> 1]) : bf_lo(v[k >> 1]));
  const uint32_t q4 = sb + aQ + slot * kQCh + (kQ4Pad + q_word(blk, 0)) * 4, q8 = q4 + (kQ4Words + kQ8Pad - kQ4Pad) * 4;
#pragma unroll
  for (int k = 0; k < 4; k++) {
    uint32_t w[4];
#pragma unroll
    for (int i = 0; i < 4; i++) {
      const int p = 16 + 2 * k + (i >> 1) + 8 * (i & 1);
      w[i] = pack_bf16(P[p + 3] - P[p - 2], P[p - 2] - P[p - 5]);
    }
    sts128(q4 ^ (k * 16), w);
    if (BOTH) {
#pragma unroll
      for (int i = 0; i < 4; i++) {
        const int p = 16 + 2 * k + (i >> 1) + 8 * (i & 1);
        w[i] = pack_bf16(P[p + 5] - P[p - 4], P[p - 4] - P[p - 11]);
      }
      sts128(q8 ^ (k * 16), w);
    }
  }
}

struct SsmArgs {
  const __nv_bfloat16 *x, *ldt, *are, *aim;
  uint32_t zero;
  const __nv_bfloat16 *dsk, *bre, *bim, *cre, *cim;
  const char *w1, *w3;
  uint4* uT;
};

__device__ __forceinline__ void put2(uint32_t a, const Cx& u, const Cx& v) { sts64(a, pack_bf16(u.r, u.i), pack_bf16(v.r, v.i)); }

__device__ __forceinline__ void helper_jobs(uint32_t sb, int b, int warp, int lane) {
  const uint32_t nh = (b & 1) ? 0x505558u : 0x506065u, nl = (b & 1) ? 0x101414u : 0x105140u;
  const int sh = 2 * (warp - 12);
  const uint32_t below = (1u << sh) - 1;
  int job = __popc(nh & below & 0x555555u) + 2 * __popc(nh & below & 0xaaaaaau);
  if (warp == 12) {
    const uint32_t zz[4] = {0, 0, 0, 0};
#pragma unroll
    for (int s = 0; s < 5; s++) {
      const uint32_t qb = sb + aQ + s * kQCh + 16 * lane;
      if (lane < 24) sts128(qb + (lane < 16 ? 0 : 1536 * 4), zz);
      sts128(qb + kQ4Words * 4, zz);
    }
    __syncwarp();
    if (lane < 5) {
      uint32_t v[4], w[4];
      lds128(v, u_base(sb, slot_channel(b, lane)));
      const float p0 = bf_lo(v[0]), p1 = p0 + bf_hi(v[0]), p2 = p1 + bf_lo(v[1]), p3 = p2 + bf_hi(v[1]);
      w[0] = pack_bf16(p0, 0.f); w[1] = pack_bf16(p1, 0.f); w[2] = pack_bf16(p2, 0.f); w[3] = pack_bf16(p3, 0.f);
      const uint32_t qb = sb + aQ + lane * kQCh + 4;
#pragma unroll
      for (int i = 0; i < 4; i++) {
        if (i < 2) sts32(qb + (kQ4Pad + q_word(-1, 6 + i)) * 4, w[i]);
        sts32(qb + (kQ4Words + kQ8Pad + q_word(-1, 4 + i)) * 4, w[i]);
      }
    }
  }
#pragma unroll 1
  for (int n = (nh >> sh) & 3; n > 0; n--, job++) box_job<true>(sb, b, job >> 1, (job & 1) * 32 + lane);
  if ((nl >> sh) & 1) box_job<false>(sb, b, __popc(nl & below), 64 + lane);
  __syncwarp();
  if (lane == 0) mbar_arrive(sb + aBar + 16);
}

template <int A, int B>
__device__ __forceinline__ void r_rows(uint32_t fa, Cx (&S)[2][4], const Cx (&zb)[2]) {
#pragma unroll
  for (int j = A; j < B; j++) {
    put2(fa + j * kFacRow, S[0][j & 1], S[1][j & 1]);
#pragma unroll
    for (int m = 0; m < 2; m++)
      if (j < 30) S[m][j & 1] = j == 0 ? zb[m] : cmul(S[m][j & 1], zb[m]);
  }
}
__device__ __forceinline__ void l_rows(uint32_t fl, Cx (&S)[2][4], const Cx (&za)[2], const Cx (&zb)[2]) {
#pragma unroll
  for (int k = 0; k < 11; k++) {
    if (k < 4) {
      put2(fl + 2 * k * kFacRow, S[0][k], S[1][k]);
      put2(fl + (2 * k + 1) * kFacRow, cmul(S[0][k], za[0]), cmul(S[1][k], za[1]));
      S[0][k] = cmul(S[0][k], zb[0]); S[1][k] = cmul(S[1][k], zb[1]);
      put2(fl + (8 + k) * kFacRow, S[0][k], S[1][k]);
      if (k == 3) put2(fl + 21 * kFacRow, cmul(S[0][3], csqr(za[0])), cmul(S[1][3], csqr(za[1])));
    } else {
      S[0][0] = cmul(S[0][0], zb[0]); S[1][0] = cmul(S[1][0], zb[1]);
      put2(fl + (k < 6 ? 4 + 2 * k : 10 + k) * kFacRow, S[0][0], S[1][0]);
      if (k < 6) {
        S[0][2] = cmul(S[0][2], zb[0]); S[1][2] = cmul(S[1][2], zb[1]);
        put2(fl + (5 + 2 * k) * kFacRow, S[0][2], S[1][2]);
      }
    }
  }
}

__global__ void __launch_bounds__(kSsmThreads, 1) ssm_kernel(const SsmArgs a, const __grid_constant__ CUtensorMap tmU,
                                                                const __grid_constant__ CUtensorMap tmX) {
  extern __shared__ __align__(1024) unsigned char smem_raw[];
  const uint32_t sb = smem_u32(smem_raw);
  const int b = blockIdx.x, tid = threadIdx.x;
  uint32_t xv[9], ldt, are, aim;
  if (tid < 640) {
    const int c0 = slot_channel(b, tid >> 7), p0 = c0 * kN + ((((tid >> 5) + (tid >> 7)) & 2) << 5) + (tid & 31) * 2;
    ldt = ldg16(a.ldt + c0); are = ldg32(a.are + p0); aim = ldg32(a.aim + p0);
  }
  if (tid < 512) {
    const uint32_t* xr = (const uint32_t*)a.x + (b * 16 * (kD / 2) + (tid >> 5) * 256 + tid);
#pragma unroll
    for (int i = 0; i < 9; i++) xv[i] = ldg32(xr + i * 32);
  }
  const int warp = __shfl_sync(0xffffffffu, tid >> 5, 0), lane = tid & 31;
  const uint32_t la = sb + (((lane >> 1) & 1) * 8 + 2 * (lane >> 3) + (lane & 1)) * kLnRow + ((lane >> 1) & 1) * 64 + ((lane >> 2) & 1) * 32;
  const uint32_t go = (b * kD + (lane >> 2) + (lane & 2) * 8) * 2 + (lane & 1);

  if (warp < 20) {
    const int slot = warp >> 2, role = (warp + slot) & 3, ch = slot_channel(b, slot);
    const int pi = ch * kN + (role >> 1) * 64 + lane * 2;
    auto keep = [&](uint32_t v) { return __shfl_sync(0xffffffffu, v, lane); };
    auto keepp = [&](const void* p) { return (const char*)__shfl_sync(0xffffffffu, (unsigned long long)p, lane); };
    const char* pb[5] = {keepp(a.bre + pi), keepp(a.bim + pi), keepp(a.cre + pi), keepp(a.cim + pi), keepp(a.dsk + ch)};
    const uint32_t ra = keep(sb + warp * kLnRow + (warp >> 3) * 64 + lane * 4);
    const uint32_t l = keep(la + aU + (warp >> 1) * 64 + (warp & 1) * 16);
    uint4* dst = (uint4*)keepp(a.uT + go + ((warp >> 1) * 32 + (warp & 1) * 8) * 2);
    const uint32_t fac = sb + aFac + (slot * 2 + (role >> 1)) * kFacHalf;
    const uint32_t fa = keep(fac + lane * 8 + (role & 1) * 32 * kFacRow);
    Cx za[2], zb[2], S[2][4];
    float dt = 0.f, lr[2] = {0.f, 0.f}, tn[2] = {0.f, 0.f};
    za[0] = za[1] = {0.f, 0.f};
    if (a.zero == 0) {
      dt = bf_lo(pack_bf16(expf(bf_lo(ldt)), 0.f));
      const float kr = dt * ((role & 1) ? 1.4426950408889634f : 8.f * 1.4426950408889634f);
      const float ki = dt * ((role & 1) ? -0.15915494309189535f : 8.f * 0.15915494309189535f);
      lr[0] = bf_lo(are) * kr; lr[1] = bf_hi(are) * kr; tn[0] = bf_lo(aim) * ki; tn[1] = bf_hi(aim) * ki;
      za[0] = cexp2(lr[0], tn[0]); za[1] = cexp2(lr[1], tn[1]);
    }
    uint32_t bre = 0, bim = 0, cre = 0, cim = 0, dsk = 0;
    auto load_bc = [&](uint32_t dep) {
      if (role & 1) {
        const uint32_t z = dep & a.zero;
        bre = ldg32(pb[0] + z); bim = ldg32(pb[1]); cre = ldg32(pb[2]); cim = ldg32(pb[3]); dsk = ldg16(pb[4]);
      }
    };

    if (warp < 16) {
      load_bc(xv[8]);
      float xf[18], s0 = 0.f, s1 = 0.f, q0 = 0.f, q1 = 0.f;
#pragma unroll
      for (int i = 0; i < 9; i++) {
        xf[2 * i] = bf_lo(xv[i]); xf[2 * i + 1] = bf_hi(xv[i]);
        s0 += xf[2 * i]; s1 += xf[2 * i + 1];
        q0 = fmaf(xf[2 * i], xf[2 * i], q0); q1 = fmaf(xf[2 * i + 1], xf[2 * i + 1], q1);
      }
#pragma unroll
      for (int i = 0; i < 9; i++) sts32(ra + aX + i * 128, xv[i]);
      s0 += s1; q0 += q1;
      float t = (lane & 16 ? q0 : s0) + __shfl_xor_sync(0xffffffffu, lane & 16 ? s0 : q0, 16);
#pragma unroll
      for (int m = 8; m; m >>= 1) t += __shfl_xor_sync(0xffffffffu, t, m);
      const float o = __shfl_xor_sync(0xffffffffu, t, 16);
      const float mean = (lane & 16 ? o : t) * (1.f / kD);
      const uint32_t mv = pack_bf16(mean, fmaxf((lane & 16 ? t : o) * (1.f / kD) - mean * mean, 0.f));
      float sd;
      asm("sqrt.approx.ftz.f32 %0, %1;" : "=f"(sd) : "f"(bf_lo(pack_bf16(bf_hi(mv) + 1e-5f, 0.f))));
      const float r = rcpf(bf_lo(pack_bf16(sd, 0.f))), mr = -bf_lo(mv) * r;
#pragma unroll
      for (int i = 0; i < 9; i++) sts32(ra + aU + i * 128, pack_bf16(fmaf(xf[2 * i], r, mr), fmaf(xf[2 * i + 1], r, mr)));
      bar_arrive(10, 512 + 32);
      bar_sync(9, 512 + 64);
      uint32_t v[3][4];
      ldsm4t(v[0], l);
      ldsm4t(v[1], l + 512);
      if (warp < 4) ldsm4t(v[2], l + 1024);
      stg128(dst, v[0]);
      stg128(dst + 256 * 2, v[1]);
      if (warp < 4) stg128(dst + 512 * 2, v[2]);
      bar_arrive(6, 512 + 32);
    } else {
      load_bc(ldt);
      bar_sync(0, 128 + 64);
    }
    if (role & 1) {
#pragma unroll
      for (int m = 0; m < 2; m++) {
        zb[m] = cexp2(lr[m] * 256.f, tn[m] * 256.f);
        const Cx z2 = csqr(za[m]), z4 = csqr(z2);
        const Cx c = {m ? bf_hi(cre) : bf_lo(cre), -(m ? bf_hi(cim) : bf_lo(cim))};
        const Cx d = {dt * (m ? bf_hi(bre) : bf_lo(bre)), -dt * (m ? bf_hi(bim) : bf_lo(bim))};
        S[m][0] = cmul(c, d); S[m][1] = cmul(S[m][0], z2); S[m][2] = cmul(S[m][0], z4); S[m][3] = cmul(S[m][1], z4);
      }
      l_rows(fa, S, za, zb);
      bar_arrive(11 + slot, 128);
      bar_sync(1 + slot, 128);
    } else {
#pragma unroll
      for (int m = 0; m < 2; m++) { S[m][0] = {1.f, 0.f}; S[m][1] = za[m]; zb[m] = csqr(za[m]); }
      r_rows<0, 16>(fa, S, zb);
      bar_arrive(1 + slot, 128);
      r_rows<16, 32>(fa, S, zb);
      bar_sync(11 + slot, 128);
    }
    {
      const int mt = ~role & 1;
      const bool up = role >> 1;
      float c[3][4];
#pragma unroll
      for (int n = 0; n < 3; n++) c[n][0] = c[n][1] = c[n][2] = c[n][3] = 0.f;
      const uint32_t aa = fac + (mt * 16 + (lane & 15)) * kFacRow + (lane >> 4) * 16;
      const uint32_t ba = fac + (32 + (lane & 7)) * kFacRow + (lane >> 3) * 16;
#pragma unroll
      for (int k2 = 0; k2 < 4; k2++) {
        uint32_t av[2][4], bv[3][4];
        ldsm4(av[0], aa + k2 * 64); ldsm4(av[1], aa + k2 * 64 + 32);
#pragma unroll
        for (int n = 0; n < 3; n++) ldsm4(bv[n], ba + n * 8 * kFacRow + k2 * 64);
#pragma unroll
        for (int h = 0; h < 2; h++)
#pragma unroll
          for (int n = 0; n < 3; n++) mma16816(c[n], av[h][0], av[h][1], av[h][2], av[h][3], bv[n][2 * h], bv[n][2 * h + 1]);
      }
      const uint32_t ex = fac + mt * 16 * kFacRow + lane * 8;
#pragma unroll
      for (int n = 0; n < 3; n++) sts64(ex + n * 256, __float_as_uint(up ? c[n][0] : c[n][2]), __float_as_uint(up ? c[n][1] : c[n][3]));
      bar_sync((mt ? 11 : 1) + slot, 64);
      float v0[3], v1[3];
#pragma unroll
      for (int n = 0; n < 3; n++) {
        asm volatile("ld.shared.v2.f32 {%0, %1}, [%2];" : "=f"(v0[n]), "=f"(v1[n]) : "r"(ex + (up ? -kFacHalf : kFacHalf) + n * 256) : "memory");
        v0[n] += up ? c[n][2] : c[n][0];
        v1[n] += up ? c[n][3] : c[n][1];
      }
      const int j = mt * 16 + (role >> 1) * 8 + (lane >> 2), t = lane & 3;
      const uint32_t tab = sb + aTab + slot * kTabCh;
      const float k512 = __shfl_down_sync(0xffffffffu, v1[2], 1);
      if (j + t == 0) v0[0] += bf_lo(dsk);
      if (j == 31 && t == 1) v1[1] -= k512;
      const uint32_t w0 = pack_bf16(v1[0], v0[0]), w1 = pack_bf16(v0[1], v1[1]), w2 = pack_bf16(v0[2], v1[2]);
      const uint32_t k0 = tab + (16 + 8 * j + 2 * t) * 4;
      sts16(k0, w0 >> 16); sts32(k0 + 4, w0); sts16(k0 + 10, w0);
      if (t < 2) {
        const uint32_t k1 = tab + (16 + 256 + 8 * j + 4 * t) * 4;
        if (j + t) { sts16(k1 - 4, w1); sts16(k1 + 2, w1); }
        sts16(k1, w1);
        sts32(k1 + 4, __byte_perm(w1, 0, 0x1010));
        sts32(k1 + 8, __byte_perm(w1, 0, 0x1032));
        sts16(k1 + 14, w1 >> 16);
      } else {
        sts32(tab + (kKeWords + 16 + 32 * (t - 2) + j) * 4, w1);
      }
      const uint32_t k2 = tab + (kKeWords + kCWords + 7) * 4 + (64 * t + j) * 2;
      if (t < 2 || (t == 2 && j == 0)) sts16(k2, w2);
      if (t < 2) sts16(k2 + 64, w2 >> 16);
    }
    __syncwarp();
    if (lane == 0) mbar_arrive(sb + aBar + 32 + slot * 8);
  }

  if (warp < 12) {
    bar_arrive(8, kSsmThreads);
    asm volatile("setmaxnreg.inc.sync.aligned.u32 88;");
    const unsigned long long map = (b & 1) ? 0x4fff31092ba8ull : 0x3fff20b91ca8ull;
    const int code = (int)((map >> (4 * warp)) & 15), s = code & 7, c = slot_channel(b, s);
    if (code != 15) {
      mbar_wait(sb + aBar + 32 + s * 8, 0);
      mbar_wait(sb + aBar, 0);
      if (code & 8) conv_unit<true>(sb, s, c, warp, lane, a.zero);
      else conv_unit<false>(sb, s, c, warp, lane, a.zero);
    }
  } else {
    asm volatile("setmaxnreg.dec.sync.aligned.u32 56;");
    const uint32_t z[4] = {0, 0, 0, 0};
    if (warp == 20 || warp == 21) {
      const int k = warp - 20;
      const uint32_t bar = sb + aBar + k * 8, reg = sb + (k ? aX : aU);
      const bool lead = elect_one();
      unsigned* cnt = (unsigned*)__shfl_sync(0xffffffffu, (unsigned long long)&g_cnt[k * 64], lane);
      if (lead) asm volatile("prefetch.tensormap [%0];" ::"l"(k ? &tmX : &tmU) : "memory");
      if (lead && b + k == 0) g_epoch++;
      if (k) {
        bar_arrive(8, kSsmThreads);
        bar_sync(10, 512 + 32);
        bar_sync(7, 64);
#pragma unroll 1
        for (int i = 0; i < 6; i++) {
          uint32_t v[6][4];
#pragma unroll
          for (int j = 0; j < 6; j++) ldsm4t(v[j], la + aX + i * 192 + (j >> 1) * 64 + (j & 1) * 16);
#pragma unroll
          for (int j = 0; j < 6; j++) stg128(g_xT + go + (i * 96 + (j >> 1) * 32 + (j & 1) * 8) * 2, v[j]);
        }
        __syncwarp();
      } else {
        bar_sync(6, 512 + 32);
      }
      if (lead) asm volatile("red.release.gpu.global.add.u32 [%0], 1;" ::"l"(cnt) : "memory");
      if (!k) {
#pragma unroll
        for (int s = 0; s < 4; s++) sts128(reg + (s >> 1) * kUTile + (s & 1) * 512 + lane * 16, z);
        bar_arrive(8, kSsmThreads);
      }
      __syncwarp();
      if (lead) {
        mbar_expect(bar, k ? 5 * 4096 : 2 * 16384);
        asm volatile("fence.proxy.async.shared::cta;" ::: "memory");
        flag_wait(cnt, 128, k * 50);
        asm volatile("fence.proxy.async.global;" ::: "memory");
        if (k) {
#pragma unroll 1
          for (int s = 0; s < 5; s++) tma2d(reg + s * 4096, &tmX, bar, slot_channel(b, s) * 16, 0);
        } else {
          tma2d(reg + kUPad, &tmU, bar, b * 64, 0);
          tma2d(reg + kUTile + kUPad, &tmU, bar, (128 + (b >> 3)) * 64, 0);
        }
      }
      __syncwarp();
      if (!k) {
        bar_arrive(7, 64);
#pragma unroll 1
        for (int p = 0; p < kAhead; p++) {
          const char* wp = ((p & 1) ? a.w3 : a.w1) + (size_t)((b & 15) * 36 + lane) * (kF * 2) + (b >> 4) * 1152 + hidden_block(p >> 1) * 128;
          asm volatile("prefetch.global.L2 [%0];" ::"l"(wp));
          if (lane < 4) asm volatile("prefetch.global.L2 [%0];" ::"l"(wp + 32 * kF * 2));
        }
      }
    } else {
      if (warp >= 22) {
        if (warp == 22 && elect_one()) {
          mbar_init(sb + aBar, 1); mbar_init(sb + aBar + 8, 1); mbar_init(sb + aBar + 16, 10);
#pragma unroll
          for (int s = 0; s < 5; s++) mbar_init(sb + aBar + 32 + s * 8, 4);
          asm volatile("fence.mbarrier_init.release.cluster;" ::: "memory");
        }
        __syncwarp();
#pragma unroll 1
        for (int i = tid - 704; i < 5 * kTabCh / 16; i += 64) sts128(sb + aTab + i * 16, z);
        bar_arrive(0, 128 + 64);
        bar_arrive(9, 512 + 64);
      }
      bar_sync(8, kSsmThreads);
      mbar_wait(sb + aBar, 0);
      helper_jobs(sb, b, warp, lane);
    }
  }
}

typedef CUresult (*EncodeFn)(CUtensorMap*, CUtensorMapDataType, cuuint32_t, void*, const cuuint64_t*, const cuuint64_t*,
                             const cuuint32_t*, const cuuint32_t*, CUtensorMapInterleave, CUtensorMapSwizzle,
                             CUtensorMapL2promotion, CUtensorMapFloatOOBfill);

void encode2d(EncodeFn fn, CUtensorMap* tm, void* p, int cols, int rows, int bx, int by,
              CUtensorMapL2promotion promo = CU_TENSOR_MAP_L2_PROMOTION_L2_128B) {
  cuuint64_t gd[2] = {(cuuint64_t)cols, (cuuint64_t)rows}, gs[1] = {(cuuint64_t)cols * 2};
  cuuint32_t box[2] = {(cuuint32_t)bx, (cuuint32_t)by}, es[2] = {1, 1};
  fn(tm, CU_TENSOR_MAP_DATA_TYPE_BFLOAT16, 2, p, gd, gs, box, es, CU_TENSOR_MAP_INTERLEAVE_NONE,
     bx == 64 ? CU_TENSOR_MAP_SWIZZLE_128B : CU_TENSOR_MAP_SWIZZLE_32B, promo, CU_TENSOR_MAP_FLOAT_OOB_FILL_NONE);
}

}

extern "C" void kernel_launch(void* const* d_in, const int* in_sizes, int n_in, void* d_out, int out_size) {
  typedef const __nv_bfloat16* P;
  void* fn = nullptr;
  cudaDriverEntryPointQueryResult qr;
  cudaGetDriverEntryPoint("cuTensorMapEncodeTiled", &fn, cudaEnableDefault, &qr);
  void *uT, *xT, *hT;
  cudaGetSymbolAddress(&hT, g_hT);
  cudaGetSymbolAddress(&uT, g_uT);
  cudaGetSymbolAddress(&xT, g_xT);
  CUtensorMap t1, t3, t2, tu, tx;
  encode2d((EncodeFn)fn, &tu, uT, kD * 16, 128, 64, 128, CU_TENSOR_MAP_L2_PROMOTION_NONE);
  encode2d((EncodeFn)fn, &tx, xT, kD * 16, 128, 16, 128, CU_TENSOR_MAP_L2_PROMOTION_NONE);
  encode2d((EncodeFn)fn, &t1, d_in[10], kF, kD, 64, kBoxRows);
  encode2d((EncodeFn)fn, &t3, d_in[11], kF, kD, 64, kBoxRows);
  encode2d((EncodeFn)fn, &t2, d_in[12], kD, kF, 64, kBoxRows);
  cudaFuncSetAttribute(ffn_kernel, cudaFuncAttributeMaxDynamicSharedMemorySize, kFfnSmem);

  cudaFuncSetAttribute(ssm_kernel, cudaFuncAttributeMaxDynamicSharedMemorySize, kSsmSmem);
  SsmArgs sa = {(P)d_in[0], (P)d_in[7], (P)d_in[1], (P)d_in[2], 0u, (P)d_in[8], (P)d_in[3], (P)d_in[4], (P)d_in[5], (P)d_in[6],
                (const char*)d_in[10], (const char*)d_in[11], (uint4*)uT};
  ssm_kernel<<<128, kSsmThreads, kSsmSmem, cudaStreamPerThread>>>(sa, tu, tx);

  cudaLaunchConfig_t cfg = {};
  cfg.gridDim = dim3(128);
  cfg.blockDim = dim3(384);
  cfg.dynamicSmemBytes = kFfnSmem;
  cfg.stream = cudaStreamPerThread;
  cudaLaunchAttribute at[1];
  at[0].id = cudaLaunchAttributeProgrammaticStreamSerialization;
  at[0].val.programmaticStreamSerializationAllowed = 1;
  cfg.attrs = at;
  cfg.numAttrs = 1;
  cudaLaunchKernelEx(&cfg, ffn_kernel, (const char*)hT, t1, t3, t2, (__nv_bfloat16*)d_out, 1);
}
```
